```python
import torch

def _softmax(x, axis=-1):
    return torch.softmax(x, dim=axis)
def _gelu(x):
    return torch.nn.functional.gelu(x, approximate="tanh")
def _silu(x):
    return torch.nn.functional.silu(x)
def _sigmoid(x):
    return torch.sigmoid(x)
def _layernorm(x, axis=-1, eps=1e-5):
    m = x.mean(dim=axis, keepdim=True)
    v = x.var(dim=axis, keepdim=True, unbiased=False)
    return (x - m) / torch.sqrt(v + eps)
def _scatter_add(tgt, idx, src, axis=0):
    return tgt.clone().index_add_(axis, idx, src)
def _segment_sum(src, seg, n):
    out = torch.zeros((n,) + src.shape[1:], dtype=src.dtype)
    return out.index_add_(0, seg, src)
def _pad(x, pw):
    flat = tuple(v for pair in reversed(pw) for v in pair)
    return torch.nn.functional.pad(x, flat)

kernel_name = 'sequential_preLN__sliding_local_dilated__dense_activation_relu__prompt'

def setup_inputs():

    _w = (lambda a: (lambda t: t.to(torch.bfloat16) if t.is_floating_point() else t)(torch.as_tensor(a)))
    def _A_setup():
        B, S, D = 1, 2048, 1024
        return {
            "x": _w((lambda *s: torch.randn(*s, dtype=torch.bfloat16) * 0.05)(B, S, D)),
            "wqkv": _w((lambda *s: torch.randn(*s, dtype=torch.bfloat16) * 0.05)(D, 3 * D)),
            "wo": _w((lambda *s: torch.randn(*s, dtype=torch.bfloat16) * 0.05)(D, D)),
        }
    _A_in = _A_setup()

    def _B_setup():
        B, S, D, Dff = 1, 2048, 1024, 3584
        return {
            "x": _w((lambda *s: torch.randn(*s, dtype=torch.bfloat16) * 0.05)(B, S, D)),
            "w1": _w((lambda *s: torch.randn(*s, dtype=torch.bfloat16) * 0.05)(D, Dff)),
            "w2": _w((lambda *s: torch.randn(*s, dtype=torch.bfloat16) * 0.05)(Dff, D)),
        }
    _B_in = _B_setup()

    return {
        "A_x": _A_in["x"],
        "A_wqkv": _A_in["wqkv"],
        "A_wo": _A_in["wo"],
        "B_x": _B_in["x"],
        "B_w1": _B_in["w1"],
        "B_w2": _B_in["w2"],
    }

def reference(A_x, A_wqkv, A_wo, B_x, B_w1, B_w2):
    def _A_ref(x, wqkv, wo):
        B, S, D = x.shape
        H = 32; Dh = D // H
        W, dil = 8, 2
        qkv = (lambda x, *d: x.permute(*d))((x @ wqkv).reshape(B, S, 3, H, Dh), 2, 0, 3, 1, 4)
        q, k, v = qkv[0], qkv[1], qkv[2]
        scale = Dh ** -0.5
        pos = torch.arange(S)
        off = torch.arange(W) * dil
        idx = pos[:, None] - off[None, :]
        mask = idx >= 0
        idx_c = torch.where(mask, idx, 0).reshape(-1)
        kg = k[:, :, idx_c, :].reshape(B, H, S, W, Dh)
        vg = v[:, :, idx_c, :].reshape(B, H, S, W, Dh)
        logits = torch.einsum("bhsd,bhswd->bhsw", q, kg) * scale
        logits = torch.where(mask[None, None, :, :], logits, -1e9)
        attn = _softmax(logits, axis=-1)
        o = torch.einsum("bhsw,bhswd->bhsd", attn, vg)
        return (lambda x, *d: x.permute(*d))(o, 0, 2, 1, 3).reshape(B, S, D) @ wo

    def _B_ref(x, w1, w2):
        h = torch.einsum("bsd,df->bsf", x, w1)
        zero = torch.zeros_like(h)
        h = torch.maximum(h, zero)
        return torch.einsum("bsf,fd->bsd", h, w2)

    x = A_x
    h = x + _A_ref(_layernorm(x, axis=-1), A_wqkv, A_wo)
    h2 = h + _B_ref(_layernorm(h, axis=-1), B_w1, B_w2)
    return h2
```

```cpp
#include <cuda_runtime.h>
#include <cuda_bf16.h>
#include <cuda.h>
#include <stdint.h>

namespace {

__device__ __forceinline__ void wgmma_n128(float (&d)[64], uint64_t da, uint64_t db, int scaleD) {
  asm volatile("{\n.reg .pred p;\nsetp.ne.b32 p, %66, 0;\n"
    "wgmma.mma_async.sync.aligned.m64n128k16.f32.bf16.bf16 "
    "{%0, %1, %2, %3, %4, %5, %6, %7, %8, %9, %10, %11, %12, %13, %14, %15, "
    "%16, %17, %18, %19, %20, %21, %22, %23, %24, %25, %26, %27, %28, %29, %30, %31, "
    "%32, %33, %34, %35, %36, %37, %38, %39, %40, %41, %42, %43, %44, %45, %46, %47, "
    "%48, %49, %50, %51, %52, %53, %54, %55, %56, %57, %58, %59, %60, %61, %62, %63}, "
    "%64, %65, p, 1, 1, 0, 1;\n}\n"
    : "+f"(d[0]), "+f"(d[1]), "+f"(d[2]), "+f"(d[3]), "+f"(d[4]), "+f"(d[5]), "+f"(d[6]), "+f"(d[7]),
      "+f"(d[8]), "+f"(d[9]), "+f"(d[10]), "+f"(d[11]), "+f"(d[12]), "+f"(d[13]), "+f"(d[14]), "+f"(d[15]),
      "+f"(d[16]), "+f"(d[17]), "+f"(d[18]), "+f"(d[19]), "+f"(d[20]), "+f"(d[21]), "+f"(d[22]), "+f"(d[23]),
      "+f"(d[24]), "+f"(d[25]), "+f"(d[26]), "+f"(d[27]), "+f"(d[28]), "+f"(d[29]), "+f"(d[30]), "+f"(d[31]),
      "+f"(d[32]), "+f"(d[33]), "+f"(d[34]), "+f"(d[35]), "+f"(d[36]), "+f"(d[37]), "+f"(d[38]), "+f"(d[39]),
      "+f"(d[40]), "+f"(d[41]), "+f"(d[42]), "+f"(d[43]), "+f"(d[44]), "+f"(d[45]), "+f"(d[46]), "+f"(d[47]),
      "+f"(d[48]), "+f"(d[49]), "+f"(d[50]), "+f"(d[51]), "+f"(d[52]), "+f"(d[53]), "+f"(d[54]), "+f"(d[55]),
      "+f"(d[56]), "+f"(d[57]), "+f"(d[58]), "+f"(d[59]), "+f"(d[60]), "+f"(d[61]), "+f"(d[62]), "+f"(d[63])
    : "l"(da), "l"(db), "r"(scaleD));
}

__device__ __forceinline__ void wgmma_n192(float (&d)[96], uint64_t da, uint64_t db, int scaleD) {
  asm volatile("{\n.reg .pred p;\nsetp.ne.b32 p, %98, 0;\n"
    "wgmma.mma_async.sync.aligned.m64n192k16.f32.bf16.bf16 "
    "{%0, %1, %2, %3, %4, %5, %6, %7, %8, %9, %10, %11, %12, %13, %14, %15, "
    "%16, %17, %18, %19, %20, %21, %22, %23, %24, %25, %26, %27, %28, %29, %30, %31, "
    "%32, %33, %34, %35, %36, %37, %38, %39, %40, %41, %42, %43, %44, %45, %46, %47, "
    "%48, %49, %50, %51, %52, %53, %54, %55, %56, %57, %58, %59, %60, %61, %62, %63, "
    "%64, %65, %66, %67, %68, %69, %70, %71, %72, %73, %74, %75, %76, %77, %78, %79, "
    "%80, %81, %82, %83, %84, %85, %86, %87, %88, %89, %90, %91, %92, %93, %94, %95}, "
    "%96, %97, p, 1, 1, 0, 1;\n}\n"
    : "+f"(d[0]), "+f"(d[1]), "+f"(d[2]), "+f"(d[3]), "+f"(d[4]), "+f"(d[5]), "+f"(d[6]), "+f"(d[7]),
      "+f"(d[8]), "+f"(d[9]), "+f"(d[10]), "+f"(d[11]), "+f"(d[12]), "+f"(d[13]), "+f"(d[14]), "+f"(d[15]),
      "+f"(d[16]), "+f"(d[17]), "+f"(d[18]), "+f"(d[19]), "+f"(d[20]), "+f"(d[21]), "+f"(d[22]), "+f"(d[23]),
      "+f"(d[24]), "+f"(d[25]), "+f"(d[26]), "+f"(d[27]), "+f"(d[28]), "+f"(d[29]), "+f"(d[30]), "+f"(d[31]),
      "+f"(d[32]), "+f"(d[33]), "+f"(d[34]), "+f"(d[35]), "+f"(d[36]), "+f"(d[37]), "+f"(d[38]), "+f"(d[39]),
      "+f"(d[40]), "+f"(d[41]), "+f"(d[42]), "+f"(d[43]), "+f"(d[44]), "+f"(d[45]), "+f"(d[46]), "+f"(d[47]),
      "+f"(d[48]), "+f"(d[49]), "+f"(d[50]), "+f"(d[51]), "+f"(d[52]), "+f"(d[53]), "+f"(d[54]), "+f"(d[55]),
      "+f"(d[56]), "+f"(d[57]), "+f"(d[58]), "+f"(d[59]), "+f"(d[60]), "+f"(d[61]), "+f"(d[62]), "+f"(d[63]),
      "+f"(d[64]), "+f"(d[65]), "+f"(d[66]), "+f"(d[67]), "+f"(d[68]), "+f"(d[69]), "+f"(d[70]), "+f"(d[71]),
      "+f"(d[72]), "+f"(d[73]), "+f"(d[74]), "+f"(d[75]), "+f"(d[76]), "+f"(d[77]), "+f"(d[78]), "+f"(d[79]),
      "+f"(d[80]), "+f"(d[81]), "+f"(d[82]), "+f"(d[83]), "+f"(d[84]), "+f"(d[85]), "+f"(d[86]), "+f"(d[87]),
      "+f"(d[88]), "+f"(d[89]), "+f"(d[90]), "+f"(d[91]), "+f"(d[92]), "+f"(d[93]), "+f"(d[94]), "+f"(d[95])
    : "l"(da), "l"(db), "r"(scaleD));
}

__device__ __forceinline__ void wgmma_n256(float (&d)[128], uint64_t da, uint64_t db, int scaleD) {
  asm volatile("{\n.reg .pred p;\nsetp.ne.b32 p, %130, 0;\n"
    "wgmma.mma_async.sync.aligned.m64n256k16.f32.bf16.bf16 "
    "{%0, %1, %2, %3, %4, %5, %6, %7, %8, %9, %10, %11, %12, %13, %14, %15, "
    "%16, %17, %18, %19, %20, %21, %22, %23, %24, %25, %26, %27, %28, %29, %30, %31, "
    "%32, %33, %34, %35, %36, %37, %38, %39, %40, %41, %42, %43, %44, %45, %46, %47, "
    "%48, %49, %50, %51, %52, %53, %54, %55, %56, %57, %58, %59, %60, %61, %62, %63, "
    "%64, %65, %66, %67, %68, %69, %70, %71, %72, %73, %74, %75, %76, %77, %78, %79, "
    "%80, %81, %82, %83, %84, %85, %86, %87, %88, %89, %90, %91, %92, %93, %94, %95, "
    "%96, %97, %98, %99, %100, %101, %102, %103, %104, %105, %106, %107, %108, %109, %110, %111, "
    "%112, %113, %114, %115, %116, %117, %118, %119, %120, %121, %122, %123, %124, %125, %126, %127}, "
    "%128, %129, p, 1, 1, 0, 1;\n}\n"
    : "+f"(d[0]), "+f"(d[1]), "+f"(d[2]), "+f"(d[3]), "+f"(d[4]), "+f"(d[5]), "+f"(d[6]), "+f"(d[7]),
      "+f"(d[8]), "+f"(d[9]), "+f"(d[10]), "+f"(d[11]), "+f"(d[12]), "+f"(d[13]), "+f"(d[14]), "+f"(d[15]),
      "+f"(d[16]), "+f"(d[17]), "+f"(d[18]), "+f"(d[19]), "+f"(d[20]), "+f"(d[21]), "+f"(d[22]), "+f"(d[23]),
      "+f"(d[24]), "+f"(d[25]), "+f"(d[26]), "+f"(d[27]), "+f"(d[28]), "+f"(d[29]), "+f"(d[30]), "+f"(d[31]),
      "+f"(d[32]), "+f"(d[33]), "+f"(d[34]), "+f"(d[35]), "+f"(d[36]), "+f"(d[37]), "+f"(d[38]), "+f"(d[39]),
      "+f"(d[40]), "+f"(d[41]), "+f"(d[42]), "+f"(d[43]), "+f"(d[44]), "+f"(d[45]), "+f"(d[46]), "+f"(d[47]),
      "+f"(d[48]), "+f"(d[49]), "+f"(d[50]), "+f"(d[51]), "+f"(d[52]), "+f"(d[53]), "+f"(d[54]), "+f"(d[55]),
      "+f"(d[56]), "+f"(d[57]), "+f"(d[58]), "+f"(d[59]), "+f"(d[60]), "+f"(d[61]), "+f"(d[62]), "+f"(d[63]),
      "+f"(d[64]), "+f"(d[65]), "+f"(d[66]), "+f"(d[67]), "+f"(d[68]), "+f"(d[69]), "+f"(d[70]), "+f"(d[71]),
      "+f"(d[72]), "+f"(d[73]), "+f"(d[74]), "+f"(d[75]), "+f"(d[76]), "+f"(d[77]), "+f"(d[78]), "+f"(d[79]),
      "+f"(d[80]), "+f"(d[81]), "+f"(d[82]), "+f"(d[83]), "+f"(d[84]), "+f"(d[85]), "+f"(d[86]), "+f"(d[87]),
      "+f"(d[88]), "+f"(d[89]), "+f"(d[90]), "+f"(d[91]), "+f"(d[92]), "+f"(d[93]), "+f"(d[94]), "+f"(d[95]),
      "+f"(d[96]), "+f"(d[97]), "+f"(d[98]), "+f"(d[99]), "+f"(d[100]), "+f"(d[101]), "+f"(d[102]), "+f"(d[103]),
      "+f"(d[104]), "+f"(d[105]), "+f"(d[106]), "+f"(d[107]), "+f"(d[108]), "+f"(d[109]), "+f"(d[110]), "+f"(d[111]),
      "+f"(d[112]), "+f"(d[113]), "+f"(d[114]), "+f"(d[115]), "+f"(d[116]), "+f"(d[117]), "+f"(d[118]), "+f"(d[119]),
      "+f"(d[120]), "+f"(d[121]), "+f"(d[122]), "+f"(d[123]), "+f"(d[124]), "+f"(d[125]), "+f"(d[126]), "+f"(d[127])
    : "l"(da), "l"(db), "r"(scaleD));
}

typedef __nv_bfloat16 bf16;
constexpr int S_ = 2048, D_ = 1024, F_ = 3584;
constexpr int OFF_SPARE = 160 * 1024, OFF_STG = 192 * 1024, OFF_CS = 224 * 1024, OFF_ST = OFF_CS + 1792, OFF_BAR = OFF_ST + 1024;
constexpr int SMEM_BYTES = 232448;
enum { B_FULL = 0, B_EMPTY = 8, B_SFULL = 16, B_SEMPTY = 18, B_AUXA = 20, B_AUXB = 21, B_RDY0 = 22, B_RDY1 = 23, B_SPARE = 24 };
enum { F_XS = 0, F_CS1 = 16, F_CS2 = 24, F_O = 32, F_H = 96, F_HS = 224, F_H1 = 256, F_NUM = 320 };

struct Params {
  CUtensorMap mX, mOut, mWqkv, mWo, mW1a, mW1b, mW2, mO, mH, mH1;
  const bf16* x;
  unsigned char role[64];
};

__device__ __align__(1024) bf16 g_o[S_ * D_];
__device__ __align__(1024) bf16 g_h[S_ * D_];
__device__ __align__(1024) bf16 g_h1[S_ * F_];
__device__ __align__(128) float2 g_xst[S_];
__device__ __align__(128) float2 g_hst[S_ * 8];
__device__ __align__(128) float g_cs1[16 * 3072];
__device__ __align__(128) float g_cs2[16 * F_];
__device__ __align__(128) uint4 g_halo[16 * 8 * 2 * 2 * 256];
__device__ __align__(128) uint32_t g_flag[F_NUM * 8];
__device__ uint32_t g_ctr;
#define PROF(role, idx) do {} while (0)

constexpr int SPIN_LIMIT = 1 << 22;

__device__ __forceinline__ void mbar_init(uint32_t bar, uint32_t cnt) { asm volatile("mbarrier.init.shared::cta.b64 [%0], %1;" ::"r"(bar), "r"(cnt)); }
__device__ __forceinline__ void mbar_expect_tx(uint32_t bar, uint32_t bytes) { asm volatile("mbarrier.arrive.expect_tx.shared::cta.b64 _, [%0], %1;" ::"r"(bar), "r"(bytes) : "memory"); }
__device__ __forceinline__ void mbar_arrive(uint32_t bar) { asm volatile("mbarrier.arrive.shared::cta.b64 _, [%0];" ::"r"(bar) : "memory"); }
__device__ __forceinline__ void mbar_arrive_cl(uint32_t bar_cluster_addr) { asm volatile("mbarrier.arrive.shared::cluster.b64 _, [%0];" ::"r"(bar_cluster_addr) : "memory"); }
__device__ __forceinline__ uint32_t mapa(uint32_t a, uint32_t cta) { uint32_t r; asm("mapa.shared::cluster.u32 %0, %1, %2;" : "=r"(r) : "r"(a), "r"(cta)); return r; }
__device__ __forceinline__ void mbar_wait(uint32_t bar, uint32_t parity) {
  uint32_t ok; int it = 0;
  do {
    asm volatile("{\n.reg .pred p;\nmbarrier.try_wait.parity.shared::cta.b64 p, [%1], %2;\nselp.u32 %0, 1, 0, p;\n}\n" : "=r"(ok) : "r"(bar), "r"(parity) : "memory");
    if (++it > SPIN_LIMIT) __trap();
  } while (!ok);
}
__device__ __forceinline__ void flag_add(int f) { asm volatile("red.release.gpu.global.add.u32 [%0], 1;" ::"l"(g_flag + f * 8) : "memory"); }
__device__ __forceinline__ void flag_wait(int f, uint32_t target) {
  uint32_t v; int it = 0;
  do {
    asm volatile("ld.acquire.gpu.global.u32 %0, [%1];" : "=r"(v) : "l"(g_flag + f * 8) : "memory");
    if (++it > SPIN_LIMIT) __trap();
  } while ((int)(v - target) < 0);
}
__device__ __forceinline__ void fence_async_global() { asm volatile("fence.proxy.async.global;" ::: "memory"); }
__device__ __forceinline__ void fence_async_smem() { asm volatile("fence.proxy.async.shared::cta;" ::: "memory"); }
__device__ __forceinline__ void tma2d_mc(uint32_t dst, const CUtensorMap* m, uint32_t bar, int c0, int c1) {
  asm volatile("cp.async.bulk.tensor.2d.shared::cluster.global.mbarrier::complete_tx::bytes.multicast::cluster [%0], [%1, {%3, %4}], [%2], %5;"
               ::"r"(dst), "l"(m), "r"(bar), "r"(c0), "r"(c1), "h"((uint16_t)3) : "memory");
}
__device__ __forceinline__ void tma3d(uint32_t dst, const CUtensorMap* m, uint32_t bar, int c0, int c1, int c2) {
  asm volatile("cp.async.bulk.tensor.3d.shared::cluster.global.mbarrier::complete_tx::bytes [%0], [%1, {%3, %4, %5}], [%2];"
               ::"r"(dst), "l"(m), "r"(bar), "r"(c0), "r"(c1), "r"(c2) : "memory");
}
__device__ __forceinline__ void tma3d_mc(uint32_t dst, const CUtensorMap* m, uint32_t bar, int c0, int c1, int c2) {
  asm volatile("cp.async.bulk.tensor.3d.shared::cluster.global.mbarrier::complete_tx::bytes.multicast::cluster [%0], [%1, {%3, %4, %5}], [%2], %6;"
               ::"r"(dst), "l"(m), "r"(bar), "r"(c0), "r"(c1), "r"(c2), "h"((uint16_t)3) : "memory");
}
__device__ __forceinline__ void tma3d_prefetch(const CUtensorMap* m, int c0, int c1, int c2) {
  asm volatile("cp.async.bulk.prefetch.tensor.3d.L2.global [%0, {%1, %2, %3}];" ::"l"(m), "r"(c0), "r"(c1), "r"(c2) : "memory");
}
__device__ __forceinline__ void tma2d_st(const CUtensorMap* m, uint32_t src, int c0, int c1) {
  asm volatile("cp.async.bulk.tensor.2d.global.shared::cta.bulk_group [%0, {%2, %3}], [%1];" ::"l"(m), "r"(src), "r"(c0), "r"(c1) : "memory");
}
__device__ __forceinline__ void tma3d_st(const CUtensorMap* m, uint32_t src, int c0, int c1, int c2) {
  asm volatile("cp.async.bulk.tensor.3d.global.shared::cta.bulk_group [%0, {%2, %3, %4}], [%1];" ::"l"(m), "r"(src), "r"(c0), "r"(c1), "r"(c2) : "memory");
}
__device__ __forceinline__ void bulk_ld(uint32_t dst, const void* src, uint32_t bytes, uint32_t bar) {
  asm volatile("cp.async.bulk.shared::cluster.global.mbarrier::complete_tx::bytes [%0], [%1], %2, [%3];" ::"r"(dst), "l"(src), "r"(bytes), "r"(bar) : "memory");
}
__device__ __forceinline__ void bulk_commit() { asm volatile("cp.async.bulk.commit_group;" ::: "memory"); }
__device__ __forceinline__ void bulk_wait_read() { asm volatile("cp.async.bulk.wait_group.read 0;" ::: "memory"); }
__device__ __forceinline__ void bulk_wait_all() { asm volatile("cp.async.bulk.wait_group 0;" ::: "memory"); }
__device__ __forceinline__ void wg_fence() { asm volatile("wgmma.fence.sync.aligned;" ::: "memory"); }
__device__ __forceinline__ void wg_commit() { asm volatile("wgmma.commit_group.sync.aligned;" ::: "memory"); }
template <int N> __device__ __forceinline__ void wg_wait() { asm volatile("wgmma.wait_group.sync.aligned %0;" ::"n"(N) : "memory"); }
__device__ __forceinline__ uint64_t mkdesc(uint32_t addr, uint32_t lbo) {
  return (uint64_t)(((addr & 0x3FFFF) >> 4) | ((lbo >> 4) << 16)) | ((uint64_t)(64u | (1u << 30)) << 32);
}
__device__ __forceinline__ void named_sync(int id, int n) { asm volatile("bar.sync %0, %1;" ::"r"(id), "r"(n) : "memory"); }
__device__ __forceinline__ uint32_t pack2(float lo, float hi) { uint32_t r; asm("cvt.rn.bf16x2.f32 %0, %1, %2;" : "=r"(r) : "f"(hi), "f"(lo)); return r; }
__device__ __forceinline__ uint32_t pack2_relu(float lo, float hi) { uint32_t r; asm("cvt.rn.relu.bf16x2.f32 %0, %1, %2;" : "=r"(r) : "f"(hi), "f"(lo)); return r; }
__device__ __forceinline__ float bf_lo(uint32_t v) { return __uint_as_float(v << 16); }
__device__ __forceinline__ float bf_hi(uint32_t v) { return __uint_as_float(v & 0xFFFF0000u); }
__device__ __forceinline__ void stsm4(uint32_t a, uint32_t r0, uint32_t r1, uint32_t r2, uint32_t r3) {
  asm volatile("stmatrix.sync.aligned.m8n8.x4.shared.b16 [%0], {%1, %2, %3, %4};" ::"r"(a), "r"(r0), "r"(r1), "r"(r2), "r"(r3) : "memory");
}
__device__ __forceinline__ void ldsm4t(uint32_t a, uint32_t& r0, uint32_t& r1, uint32_t& r2, uint32_t& r3) {
  asm volatile("ldmatrix.sync.aligned.m8n8.x4.trans.shared.b16 {%0, %1, %2, %3}, [%4];" : "=r"(r0), "=r"(r1), "=r"(r2), "=r"(r3) : "r"(a) : "memory");
}
__device__ __forceinline__ uint32_t movm(uint32_t a) { uint32_t d; asm volatile("movmatrix.sync.aligned.m8n8.trans.b16 %0, %1;" : "=r"(d) : "r"(a)); return d; }
__device__ __forceinline__ void mma16(float (&c)[4], uint32_t a0, uint32_t a1, uint32_t a2, uint32_t a3, uint32_t b0, uint32_t b1) {
  asm volatile("mma.sync.aligned.m16n8k16.row.col.f32.bf16.bf16.f32 {%0,%1,%2,%3}, {%4,%5,%6,%7}, {%8,%9}, {%0,%1,%2,%3};"
               : "+f"(c[0]), "+f"(c[1]), "+f"(c[2]), "+f"(c[3]) : "r"(a0), "r"(a1), "r"(a2), "r"(a3), "r"(b0), "r"(b1));
}
__device__ __forceinline__ void mma8(float (&c)[4], uint32_t a0, uint32_t a1, uint32_t b0) {
  asm volatile("mma.sync.aligned.m16n8k8.row.col.f32.bf16.bf16.f32 {%0,%1,%2,%3}, {%4,%5}, {%6}, {%0,%1,%2,%3};"
               : "+f"(c[0]), "+f"(c[1]), "+f"(c[2]), "+f"(c[3]) : "r"(a0), "r"(a1), "r"(b0));
}
__device__ __forceinline__ float2 lds64f(uint32_t a) { float2 v; asm volatile("ld.shared.v2.f32 {%0, %1}, [%2];" : "=f"(v.x), "=f"(v.y) : "r"(a)); return v; }
__device__ __forceinline__ uint4 lds128(uint32_t a) { uint4 v; asm volatile("ld.shared.v4.b32 {%0, %1, %2, %3}, [%4];" : "=r"(v.x), "=r"(v.y), "=r"(v.z), "=r"(v.w) : "r"(a)); return v; }
__device__ __forceinline__ void sts128(uint32_t a, uint32_t x, uint32_t y, uint32_t z, uint32_t w) { asm volatile("st.shared.v4.b32 [%0], {%1, %2, %3, %4};" ::"r"(a), "r"(x), "r"(y), "r"(z), "r"(w) : "memory"); }
__device__ __forceinline__ void sts64f(uint32_t a, float x, float y) { asm volatile("st.shared.v2.f32 [%0], {%1, %2};" ::"r"(a), "f"(x), "f"(y) : "memory"); }
__device__ __forceinline__ float4 ldcg128f(const void* p) { float4 v; asm volatile("ld.global.cg.v4.f32 {%0, %1, %2, %3}, [%4];" : "=f"(v.x), "=f"(v.y), "=f"(v.z), "=f"(v.w) : "l"(p)); return v; }
__device__ __forceinline__ uint32_t ldcg32(const void* p) { uint32_t v; asm volatile("ld.global.cg.b32 %0, [%1];" : "=r"(v) : "l"(p)); return v; }

template <int N> struct WG;
template <> struct WG<2> { static __device__ __forceinline__ void mma(float (&d)[64], uint64_t a, uint64_t b, int s) { wgmma_n128(d, a, b, s); } };
template <> struct WG<3> { static __device__ __forceinline__ void mma(float (&d)[96], uint64_t a, uint64_t b, int s) { wgmma_n192(d, a, b, s); } };
template <> struct WG<4> { static __device__ __forceinline__ void mma(float (&d)[128], uint64_t a, uint64_t b, int s) { wgmma_n256(d, a, b, s); } };

template <int PH> struct Geo {
  static constexpr int N0 = PH * 16;
  static constexpr int NS = PH == 5 ? 56 : 16;
  static constexpr int NCH = (PH == 2 || PH == 5) ? 2 : (PH == 3 ? 4 : 3);
  static constexpr int SB = 16384 + NCH * 8192;
  static constexpr int DEPTH = NCH == 2 ? 6 : 4;
  static constexpr int SLOT0 = PH == 3 ? 3 : 0;
  static __device__ __forceinline__ int dep(int m) {
    if (m >= DEPTH || PH <= 1) return N0 + m - DEPTH;
    if (PH == 2 || PH == 5) return N0 - 4 + (m < 3 ? m : 3);
    if (PH == 3) return m == 0 ? N0 - 5 : N0 - 4 + m;
    return N0 - 3 + (m < 2 ? m : 2);
  }
  static __device__ __forceinline__ int koff(int m) {
    if (PH == 2) return m < 8 ? 128 * m : 128 * (m - 8) + 64;
    if (PH == 5) return m < 32 ? 448 * (m >> 2) + 64 * (m & 3) : 448 * ((m - 32) / 3) + 256 + 64 * ((m - 32) % 3);
    return 64 * m;
  }
};

struct Ctx { uint32_t sb, bar, ep1; int i, j, rank; };

template <int PH> __device__ __forceinline__ void produce_b(const Params& p, const Ctx& c) {
  using G = Geo<PH>;
  int slot = G::SLOT0;
#pragma unroll 1
  for (int m = 0; m < G::NS; m++) {
    const int n = G::N0 + m, d = G::dep(m);
    if (d >= 0) mbar_wait(c.bar + 8 * (B_EMPTY + (d & 7)), (d >> 3) & 1);
    if (PH == 5 && m == 5) { mbar_wait(c.bar + 8 * B_SEMPTY, 0); mbar_wait(c.bar + 8 * (B_SEMPTY + 1), 0); }
    const uint32_t fb = c.bar + 8 * (n & 7), dst = c.sb + slot * G::SB + 16384;
    mbar_expect_tx(fb, G::SB);
    const int k0 = G::koff(m);
    if (PH <= 1) tma3d(dst, &p.mWqkv, fb, 128 * c.j + 64 * PH, k0, 0);
    if (PH == 2) tma3d(dst, &p.mWo, fb, 0, k0, 2 * c.j);
    if (PH == 3) tma3d(dst, &p.mW1a, fb, 0, k0, 7 * c.j);
    if (PH == 4) tma3d(dst, &p.mW1b, fb, 0, k0, 7 * c.j + 4);
    if (PH == 5) tma3d(dst, &p.mW2, fb, 0, k0, 2 * c.j);
    if (PH == 1 && m == 0) tma3d_prefetch(&p.mWo, 0, 64 * c.i, 2 * c.j);
    if (PH == 3 && (m & 3) == 3 && c.i + 4 * (m & 12) < 56) tma3d_prefetch(&p.mW2, 0, Geo<5>::koff(c.i + 4 * (m & 12)), 2 * c.j);
    if (++slot == G::DEPTH) slot = 0;
  }
}
template <int PH> __device__ __forceinline__ void produce_a(const Params& p, const Ctx& c) {
  using G = Geo<PH>;
  int slot = G::SLOT0;
  const int row = 128 * c.i + 64 * c.rank;
#pragma unroll 1
  for (int m = 0; m < G::NS; m++) {
    const int n = G::N0 + m, d = G::dep(m);
    if (PH == 2 && (m & 7) == 0) { flag_wait(F_O + (c.i * 2 + (m >> 3)) * 2 + c.rank, 8 * c.ep1); fence_async_global(); PROF(3, 0 + (m >> 3)); }
    if (PH == 3 && (m & 1) == 0) { flag_wait(F_H + c.i * 8 + (m >> 1), 2 * c.ep1); fence_async_global(); if (m == 0) PROF(3, 2); if (m == 14) PROF(3, 3); }
    if (PH == 5 && (m & 31) == 0) { flag_wait(F_H1 + (c.i * 2 + (m >> 5)) * 2 + c.rank, 8 * c.ep1); fence_async_global(); PROF(3, 4 + (m >> 5)); }
    if (d >= 0) mbar_wait(c.bar + 8 * (B_EMPTY + (d & 7)), (d >> 3) & 1);
    const uint32_t fb = c.bar + 8 * (n & 7), dst = c.sb + slot * G::SB + c.rank * 8192;
    const int k0 = G::koff(m);
    if (PH <= 1) tma3d_mc(dst, &p.mX, fb, k0, c.rank, 64 * c.i);
    if (PH == 2) tma2d_mc(dst, &p.mO, fb, k0, row);
    if (PH == 3 || PH == 4) tma2d_mc(dst, &p.mH, fb, k0, row);
    if (PH == 5) tma2d_mc(dst, &p.mH1, fb, k0, row);
    if (++slot == G::DEPTH) slot = 0;
  }
}

template <int PH> __device__ __forceinline__ void mainloop(float (&acc)[Geo<PH>::NCH * 32], const Ctx& c, int wg, uint32_t rel, bool do_rel) {
  using G = Geo<PH>;
  int slot = G::SLOT0;
#pragma unroll 1
  for (int m = 0; m < G::NS; m++) {
    const int n = G::N0 + m;
    mbar_wait(c.bar + 8 * (n & 7), (n >> 3) & 1);
    if (m == 0 && do_rel) PROF(wg, 3 * PH);
    const uint32_t sa = c.sb + slot * G::SB + wg * 8192, sbb = c.sb + slot * G::SB + 16384;
    wg_fence();
#pragma unroll
    for (int kk = 0; kk < 4; kk++) WG<G::NCH>::mma(acc, mkdesc(sa + kk * 32, 16), mkdesc(sbb + kk * 2048, 8192), (m | kk) ? 1 : 0);
    wg_commit();
    if (PH == 1 && m == 12) mbar_wait(c.bar + 8 * B_SPARE, 0);
    if (PH == 4 && m == 8) mbar_wait(c.bar + 8 * (B_SEMPTY + wg), 1);
    wg_wait<1>();
    if (m > 0 && do_rel) mbar_arrive_cl(rel + 8 * ((n - 1) & 7));
    if (++slot == G::DEPTH) slot = 0;
  }
  wg_wait<0>();
  if (do_rel) mbar_arrive_cl(rel + 8 * ((G::N0 + G::NS - 1) & 7));
  if (do_rel) PROF(wg, 3 * PH + 1);
}

__device__ __forceinline__ void handoff(const Ctx& c, int wg, int lane) {
  fence_async_smem();
  __syncwarp();
  if (lane == 0) mbar_arrive(c.bar + 8 * (B_SFULL + wg));
}

template <int T> __device__ __forceinline__ void epi_attn(float (&acc)[96], const Ctx& c, int wg, int w, int lane) {
  const int r = lane >> 2, q = lane & 3;
  if (T == 0) mbar_wait(c.bar + 8 * B_RDY0, 0); else mbar_wait(c.bar + 8 * (B_SEMPTY + wg), 0);
  const float2 s0 = lds64f(c.sb + OFF_ST + (wg * 64 + w * 16 + r) * 8), s1 = lds64f(c.sb + OFF_ST + (wg * 64 + w * 16 + r + 8) * 8);
  const uint32_t csa = c.sb + OFF_CS + (T * 192 + 2 * q) * 4;
  uint32_t pk[24][2];
#pragma unroll
  for (int tt = 0; tt < 24; tt++) {
    const int t = (tt + 8) % 24;
    const float2 cs = lds64f(csa + t * 32);
    pk[t][0] = pack2(fmaf(-s0.x, cs.x, acc[4 * t]) * s0.y, fmaf(-s0.x, cs.y, acc[4 * t + 1]) * s0.y);
    pk[t][1] = pack2(fmaf(-s1.x, cs.x, acc[4 * t + 2]) * s1.y, fmaf(-s1.x, cs.y, acc[4 * t + 3]) * s1.y);
    if (t >= 16) { pk[t][0] = movm(pk[t][0]); pk[t][1] = movm(pk[t][1]); }
    if (t == 23) {
      if (w < 3) {
        const uint32_t ha = c.sb + OFF_STG + wg * 16384 + 8192 + w * 2048 + lane * 16;
#pragma unroll
        for (int u = 0; u < 4; u++) sts128(ha + u * 512, pk[8 + 4 * u][1], pk[9 + 4 * u][1], pk[10 + 4 * u][1], pk[11 + 4 * u][1]);
      } else if (c.i < 15) {
        uint4* hp = g_halo + (((c.i * 8 + c.j) * 2 + T) * 2 + wg) * 256 + lane;
#pragma unroll
        for (int u = 0; u < 8; u++) {
          const unsigned long long a = ((unsigned long long)c.ep1 << 32) | pk[8 + 2 * u][1], b = ((unsigned long long)c.ep1 << 32) | pk[9 + 2 * u][1];
          asm volatile("st.relaxed.gpu.global.v2.b64 [%0], {%1, %2};" ::"l"(hp + u * 32), "l"(a), "l"(b) : "memory");
        }
      }
    }
  }
  named_sync(1 + wg, 128);
  uint32_t hl[16];
  if (w > 0) {
    const uint32_t ha = c.sb + OFF_STG + wg * 16384 + 8192 + (w - 1) * 2048 + lane * 16;
#pragma unroll
    for (int u = 0; u < 4; u++) { const uint4 v = lds128(ha + u * 512); hl[4 * u] = v.x; hl[4 * u + 1] = v.y; hl[4 * u + 2] = v.z; hl[4 * u + 3] = v.w; }
  } else if (c.i > 0) {
    const uint4* hp = g_halo + ((((c.i - 1) * 8 + c.j) * 2 + T) * 2 + wg) * 256 + lane;
    int it = 0; bool ok;
    do {
      ok = true;
#pragma unroll
      for (int u = 0; u < 8; u++) {
        unsigned long long a, b;
        asm volatile("ld.relaxed.gpu.global.v2.b64 {%0, %1}, [%2];" : "=l"(a), "=l"(b) : "l"(hp + u * 32) : "memory");
        hl[2 * u] = (uint32_t)a; hl[2 * u + 1] = (uint32_t)b;
        ok = ok && (uint32_t)(a >> 32) == c.ep1 && (uint32_t)(b >> 32) == c.ep1;
      }
      if (++it > SPIN_LIMIT) __trap();
    } while (!ok);
    __syncwarp();
  } else {
#pragma unroll
    for (int u = 0; u < 16; u++) hl[u] = 0;
  }
  const bool nohalo = (w == 0 && c.i == 0);
  const bool g0 = 2 * q > r, g1 = 2 * q + 1 > r;
  const float SC = 0.17677669529663687f, L2E = 1.4426950408889634f;
  const uint32_t oa = c.sb + OFF_STG + wg * 16384 + (w * 16 + (lane & 15)) * 128;
#pragma unroll
  for (int hd = 0; hd < 2; hd++) {
    float sh[4] = {0.f, 0.f, 0.f, 0.f}, sa[4] = {0.f, 0.f, 0.f, 0.f}, sb[4] = {0.f, 0.f, 0.f, 0.f};
#pragma unroll
    for (int ks = 0; ks < 2; ks++) {
      const int t = 4 * hd + 2 * ks;
      mma16(sa, pk[t][0], pk[t][1], pk[t + 1][0], pk[t + 1][1], pk[8 + t][0], pk[9 + t][0]);
      mma16(sb, pk[t][0], pk[t][1], pk[t + 1][0], pk[t + 1][1], pk[8 + t][1], pk[9 + t][1]);
      mma16(sh, pk[t][0], pk[t][1], pk[t + 1][0], pk[t + 1][1], hl[t], hl[t + 1]);
    }
    float l0 = (g0 ? sh[0] : sa[0]) * SC, l1 = (g1 ? sh[1] : sa[1]) * SC, l2 = (g0 ? sa[2] : sb[2]) * SC, l3 = (g1 ? sa[3] : sb[3]) * SC;
    if (nohalo) { if (g0) l0 = -1e9f; if (g1) l1 = -1e9f; }
    float m0 = fmaxf(l0, l1), m1 = fmaxf(l2, l3);
    m0 = fmaxf(m0, __shfl_xor_sync(~0u, m0, 1)); m1 = fmaxf(m1, __shfl_xor_sync(~0u, m1, 1));
    m0 = fmaxf(m0, __shfl_xor_sync(~0u, m0, 2)); m1 = fmaxf(m1, __shfl_xor_sync(~0u, m1, 2));
    l0 = exp2f((l0 - m0) * L2E); l1 = exp2f((l1 - m0) * L2E); l2 = exp2f((l2 - m1) * L2E); l3 = exp2f((l3 - m1) * L2E);
    float d0 = l0 + l1, d1 = l2 + l3;
    d0 += __shfl_xor_sync(~0u, d0, 1); d1 += __shfl_xor_sync(~0u, d1, 1);
    d0 += __shfl_xor_sync(~0u, d0, 2); d1 += __shfl_xor_sync(~0u, d1, 2);
    d0 = __frcp_rn(d0); d1 = __frcp_rn(d1);
    l0 *= d0; l1 *= d0; l2 *= d1; l3 *= d1;
    const uint32_t ph = pack2(g0 ? l0 : 0.f, g1 ? l1 : 0.f), pa0 = pack2(g0 ? 0.f : l0, g1 ? 0.f : l1);
    const uint32_t pa1 = pack2(g0 ? l2 : 0.f, g1 ? l3 : 0.f), pb = pack2(g0 ? 0.f : l2, g1 ? 0.f : l3);
    uint32_t ob[4][2];
#pragma unroll
    for (int nt = 0; nt < 4; nt++) {
      const int t = 4 * hd + nt;
      float o[4] = {0.f, 0.f, 0.f, 0.f};
      mma16(o, ph, 0u, pa0, pa1, hl[8 + t], pk[16 + t][0]);
      mma8(o, 0u, pb, pk[16 + t][1]);
      ob[nt][0] = pack2(o[0], o[1]); ob[nt][1] = pack2(o[2], o[3]);
    }
#pragma unroll
    for (int u = 0; u < 2; u++) stsm4(oa + (((4 * hd + 2 * u + (lane >> 4)) ^ (lane & 7)) << 4), ob[2 * u][0], ob[2 * u][1], ob[2 * u + 1][0], ob[2 * u + 1][1]);
  }
  handoff(c, wg, lane);
}

__device__ __forceinline__ void epi_res(float (&acc)[64], const uint32_t (&res)[32], float sc0, float sc1, const Ctx& c, int wg, int w, int lane) {
  const uint32_t oa = c.sb + OFF_STG + wg * 16384 + (w * 16 + (lane & 15)) * 128;
#pragma unroll
  for (int u = 0; u < 8; u++) {
    uint32_t v[4];
#pragma unroll
    for (int e = 0; e < 4; e++) {
      const int t = 2 * u + (e >> 1), hh = e & 1;
      const float sc = hh ? sc1 : sc0;
      v[e] = pack2(fmaf(sc, acc[4 * t + 2 * hh], bf_lo(res[2 * t + hh])), fmaf(sc, acc[4 * t + 2 * hh + 1], bf_hi(res[2 * t + hh])));
    }
    stsm4(oa + (u >> 2) * 8192 + ((((2 * u & 7) + (lane >> 4)) ^ (lane & 7)) << 4), v[0], v[1], v[2], v[3]);
  }
  handoff(c, wg, lane);
}

template <int NCH> __device__ __forceinline__ void epi_ffn1(float (&acc)[NCH * 32], const Ctx& c, int wg, int w, int lane) {
  const int r = lane >> 2, q = lane & 3;
  const float m0 = lds64f(c.sb + OFF_ST + (wg * 64 + w * 16 + r) * 8).x, m1 = lds64f(c.sb + OFF_ST + (wg * 64 + w * 16 + r + 8) * 8).x;
  const uint32_t csa = c.sb + OFF_CS + ((NCH == 4 ? 0 : 256) + 2 * q) * 4;
  const uint32_t rowo = (w * 16 + (lane & 15)) * 128;
#pragma unroll
  for (int u = 0; u < NCH * 4; u++) {
    const int ch = u >> 2;
    const uint32_t cb = ch < 2 ? c.sb + OFF_STG + wg * 16384 + ch * 8192 : c.sb + OFF_SPARE + wg * 8192 + (ch == NCH - 1 ? 16384 : 0);
    if (NCH == 4 && u == 8) mbar_wait(c.bar + 8 * (B_EMPTY + (60 & 7)), (60 >> 3) & 1);
    const float2 ca = lds64f(csa + 2 * u * 32), cb2 = lds64f(csa + (2 * u + 1) * 32);
    const int t = 8 * u;
    stsm4(cb + rowo + ((((2 * u & 7) + (lane >> 4)) ^ (lane & 7)) << 4),
          pack2_relu(fmaf(-m0, ca.x, acc[t]), fmaf(-m0, ca.y, acc[t + 1])), pack2_relu(fmaf(-m1, ca.x, acc[t + 2]), fmaf(-m1, ca.y, acc[t + 3])),
          pack2_relu(fmaf(-m0, cb2.x, acc[t + 4]), fmaf(-m0, cb2.y, acc[t + 5])), pack2_relu(fmaf(-m1, cb2.x, acc[t + 6]), fmaf(-m1, cb2.y, acc[t + 7])));
  }
  handoff(c, wg, lane);
}

__device__ __forceinline__ void colsum(uint32_t base, int nch, float* dst, int a, int lane) {
  const uint32_t one = 0x3F803F80u;
#pragma unroll 1
  for (int ch = 0; ch < nch; ch++) {
    float s[4][4];
#pragma unroll
    for (int t = 0; t < 4; t++) s[t][0] = s[t][1] = s[t][2] = s[t][3] = 0.f;
#pragma unroll
    for (int ks = 0; ks < 4; ks++)
#pragma unroll
      for (int u = 0; u < 2; u++) {
        uint32_t b0, b1, b2, b3;
        ldsm4t(base + ch * 8192 + (ks * 16 + (lane & 15)) * 128 + (((4 * a + 2 * u + (lane >> 4)) ^ (lane & 7)) << 4), b0, b1, b2, b3);
        mma16(s[2 * u], one, one, one, one, b0, b1);
        mma16(s[2 * u + 1], one, one, one, one, b2, b3);
      }
    if (lane < 4) {
#pragma unroll
      for (int t = 0; t < 4; t++) *reinterpret_cast<float2*>(dst + ch * 64 + 32 * a + 8 * t + 2 * lane) = make_float2(s[t][0], s[t][1]);
    }
  }
}
__device__ __forceinline__ void colsum_final(const float* src, int stride, int n4, uint32_t dst, int tid) {
#pragma unroll 1
  for (int idx = tid; idx < n4; idx += 64) {
    float4 s = make_float4(0.f, 0.f, 0.f, 0.f);
#pragma unroll
    for (int hh = 0; hh < 2; hh++) {
      float4 v[8];
#pragma unroll
      for (int u = 0; u < 8; u++) v[u] = ldcg128f(src + (hh * 8 + u) * stride + idx * 4);
#pragma unroll
      for (int u = 0; u < 8; u++) { s.x += v[u].x; s.y += v[u].y; s.z += v[u].z; s.w += v[u].w; }
    }
    sts128(dst + idx * 16, __float_as_uint(s.x), __float_as_uint(s.y), __float_as_uint(s.z), __float_as_uint(s.w));
  }
}
__device__ __forceinline__ float sum8(const uint4& v) {
  return ((bf_lo(v.x) + bf_hi(v.x)) + (bf_lo(v.y) + bf_hi(v.y))) + ((bf_lo(v.z) + bf_hi(v.z)) + (bf_lo(v.w) + bf_hi(v.w)));
}
__device__ __forceinline__ float sq2(uint32_t v, float m, float a) { const float x = bf_lo(v) - m, y = bf_hi(v) - m; return fmaf(y, y, fmaf(x, x, a)); }
__device__ __forceinline__ float sq8(const uint4& v, float m) { return sq2(v.y, m, sq2(v.x, m, 0.f)) + sq2(v.w, m, sq2(v.z, m, 0.f)); }
__device__ __forceinline__ float warp_sum(float v) {
#pragma unroll
  for (int o = 16; o; o >>= 1) v += __shfl_xor_sync(~0u, v, o);
  return v;
}

__device__ __forceinline__ void aux_warp(const Params& p, const Ctx& c, int a, int lane) {
  const uint32_t spare = c.sb + OFF_SPARE, stg = c.sb + OFF_STG, mystg = stg + a * 16384;
  const uint32_t bA = c.bar + 8 * B_AUXA, bB = c.bar + 8 * B_AUXB, bSF = c.bar + 8 * (B_SFULL + a), bSE = c.bar + 8 * (B_SEMPTY + a);
  const bool lead = (a == 0 && lane == 0);
  const int row0 = 128 * c.i + 64 * a;
  if (lead) {
    mbar_expect_tx(bA, 32768); bulk_ld(spare, p.x + (size_t)(128 * c.i + 16 * c.j) * D_, 32768, bA);
    mbar_expect_tx(bB, 24576); tma3d(stg, &p.mWqkv, bB, 128 * c.j, 64 * c.i, 0);
  }
  __syncwarp();
  mbar_wait(bA, 0);
#pragma unroll 2
  for (int u = 0; u < 8; u++) {
    const int rr = 8 * a + u;
    uint4 v[4];
#pragma unroll
    for (int e = 0; e < 4; e++) v[e] = lds128(spare + rr * 2048 + e * 512 + lane * 16);
    const float mean = warp_sum((sum8(v[0]) + sum8(v[1])) + (sum8(v[2]) + sum8(v[3]))) * (1.f / D_);
    const float var = warp_sum((sq8(v[0], mean) + sq8(v[1], mean)) + (sq8(v[2], mean) + sq8(v[3], mean))) * (1.f / D_);
    const int rb = 16 * c.j + rr;
    if (lane == 0) g_xst[128 * c.i + 64 * (rb & 1) + (rb >> 1)] = make_float2(mean, 1.f / sqrtf(var + 1e-5f));
  }
  if (lane == 0) flag_add(F_XS + c.i);
  named_sync(3, 64);
  if (lead) { mbar_expect_tx(bA, 24576); tma3d(spare, &p.mWqkv, bA, 128 * c.j + 64, 64 * c.i, 0); }
  __syncwarp();
  float* cs1 = g_cs1 + c.i * 3072 + c.j * 384;
  mbar_wait(bB, 0); colsum(stg, 3, cs1, a, lane);
  mbar_wait(bA, 1); colsum(spare, 3, cs1 + 192, a, lane);
  __syncwarp();
  if (lane == 0) flag_add(F_CS1 + c.j);
  named_sync(3, 64);
  if (lead) { mbar_expect_tx(bA, 32768); tma3d(spare, &p.mW1a, bA, 0, 64 * c.i, 7 * c.j); }
  if (lane == 0) { flag_wait(F_XS + c.i, 16 * c.ep1); flag_wait(F_CS1 + c.j, 32 * c.ep1); }
  __syncwarp();
  {
    const float4 v = ldcg128f(g_xst + row0 + 2 * lane);
    sts128(c.sb + OFF_ST + (64 * a + 2 * lane) * 8, __float_as_uint(v.x), __float_as_uint(v.y), __float_as_uint(v.z), __float_as_uint(v.w));
  }
  colsum_final(g_cs1 + c.j * 384, 3072, 96, c.sb + OFF_CS, a * 32 + lane);
  __syncwarp();
  if (lane == 0) { mbar_arrive(c.bar + 8 * B_RDY0); if (a == 0) PROF(2, 0); }
  float* cs2 = g_cs2 + c.i * F_ + c.j * 448;
  mbar_wait(bA, 0); colsum(spare, 4, cs2, a, lane);
  named_sync(3, 64);
  if (lead) { mbar_expect_tx(bA, 24576); tma3d(spare, &p.mW1b, bA, 0, 64 * c.i, 7 * c.j + 4); }
  __syncwarp();
  mbar_wait(bA, 1); colsum(spare, 3, cs2 + 256, a, lane);
  __syncwarp();
  if (lane == 0) { mbar_arrive(c.bar + 8 * B_SPARE); flag_add(F_CS2 + c.j); if (a == 0) PROF(2, 1); }
#pragma unroll 1
  for (int t = 0; t < 2; t++) {
    mbar_wait(bSF, t);
    if (lane == 0) {
      tma2d_st(&p.mO, mystg, 128 * c.j + 64 * t, row0); bulk_commit();
      bulk_wait_read(); mbar_arrive(bSE);
      bulk_wait_all(); flag_add(F_O + (c.i * 2 + t) * 2 + a);
      if (a == 0) PROF(2, 2 + t);
    }
    __syncwarp();
  }
  named_sync(3, 64);
  if (lane == 0) flag_wait(F_CS2 + c.j, 32 * c.ep1);
  __syncwarp();
  colsum_final(g_cs2 + c.j * 448, F_, 112, c.sb + OFF_CS, a * 32 + lane);
  mbar_wait(bSF, 0);
  if (lane == 0) {
    if (a == 0) PROF(2, 4);
    tma2d_st(&p.mH, mystg, 128 * c.j, row0); tma2d_st(&p.mH, mystg + 8192, 128 * c.j + 64, row0); bulk_commit();
    bulk_wait_all(); flag_add(F_H + c.i * 8 + c.j);
    if (a == 0) PROF(2, 5);
  }
  __syncwarp();
#pragma unroll 1
  for (int hh = 0; hh < 2; hh++) {
    const int rr = lane + 32 * hh;
    const uint32_t ra = mystg + rr * 128;
    float s = 0.f, m2 = 0.f;
#pragma unroll 4
    for (int u = 0; u < 16; u++) s += sum8(lds128(ra + (u >> 3) * 8192 + (((u & 7) ^ (lane & 7)) << 4)));
    const float lm = s * (1.f / 128);
#pragma unroll 4
    for (int u = 0; u < 16; u++) m2 += sq8(lds128(ra + (u >> 3) * 8192 + (((u & 7) ^ (lane & 7)) << 4)), lm);
    g_hst[(row0 + rr) * 8 + c.j] = make_float2(lm, m2);
  }
  __syncwarp();
  if (lane == 0) { mbar_arrive(bSE); flag_add(F_HS + c.i * 2 + a); flag_wait(F_HS + c.i * 2 + a, 8 * c.ep1); }
  __syncwarp();
#pragma unroll 1
  for (int hh = 0; hh < 2; hh++) {
    const int rr = lane + 32 * hh;
    float4 v[4];
#pragma unroll
    for (int u = 0; u < 4; u++) v[u] = ldcg128f(g_hst + (row0 + rr) * 8 + 2 * u);
    const float mean = (((v[0].x + v[0].z) + (v[1].x + v[1].z)) + ((v[2].x + v[2].z) + (v[3].x + v[3].z))) * 0.125f;
    float m2 = 0.f, dd = 0.f;
#pragma unroll
    for (int u = 0; u < 4; u++) { m2 += v[u].y + v[u].w; dd += (v[u].x - mean) * (v[u].x - mean) + (v[u].z - mean) * (v[u].z - mean); }
    sts64f(c.sb + OFF_ST + (64 * a + rr) * 8, mean, 1.f / sqrtf((m2 + 128.f * dd) * (1.f / D_) + 1e-5f));
  }
  __syncwarp();
  if (lane == 0) {
    mbar_arrive(c.bar + 8 * B_RDY1);
    if (a == 0) PROF(2, 6);
    mbar_wait(bSF, 1);
    tma2d_st(&p.mH1, mystg, 448 * c.j, row0); tma2d_st(&p.mH1, mystg + 8192, 448 * c.j + 64, row0);
    tma2d_st(&p.mH1, spare + a * 8192, 448 * c.j + 128, row0); tma2d_st(&p.mH1, spare + 16384 + a * 8192, 448 * c.j + 192, row0);
    bulk_commit(); bulk_wait_read(); mbar_arrive(bSE);
    bulk_wait_all(); flag_add(F_H1 + (c.i * 2 + 0) * 2 + a);
    if (a == 0) PROF(2, 7);
    mbar_wait(bSF, 0);
    tma2d_st(&p.mH1, mystg, 448 * c.j + 256, row0); tma2d_st(&p.mH1, mystg + 8192, 448 * c.j + 320, row0);
    tma2d_st(&p.mH1, spare + 16384 + a * 8192, 448 * c.j + 384, row0);
    bulk_commit(); bulk_wait_read(); mbar_arrive(bSE);
    bulk_wait_all(); flag_add(F_H1 + (c.i * 2 + 1) * 2 + a);
    if (a == 0) PROF(2, 8);
    mbar_wait(bSF, 1);
    tma3d_st(&p.mOut, mystg, 128 * c.j, a, 64 * c.i); tma3d_st(&p.mOut, mystg + 8192, 128 * c.j + 64, a, 64 * c.i);
    bulk_commit(); bulk_wait_all();
    if (a == 0) PROF(2, 9);
  }
  __syncwarp();
}

__global__ void __cluster_dims__(2, 1, 1) __launch_bounds__(384, 1) fused_block_kernel(const __grid_constant__ Params p) {
  extern __shared__ __align__(1024) uint8_t smem_raw[];
  Ctx c;
  c.sb = (uint32_t)__cvta_generic_to_shared(smem_raw);
  c.bar = c.sb + OFF_BAR;
  c.rank = blockIdx.x & 1;
  const int role = p.role[blockIdx.x >> 1];
  c.i = role & 15; c.j = (role >> 4) * 2 + c.rank;
  const int warp = threadIdx.x >> 5, lane = threadIdx.x & 31;
  if (threadIdx.x == 0) {
    PROF(2, 10);
    if (c.sb & 1023) __trap();
    for (int s = 0; s < 8; s++) { mbar_init(c.bar + 8 * (B_FULL + s), 1); mbar_init(c.bar + 8 * (B_EMPTY + s), 4); }
    for (int s = 0; s < 2; s++) { mbar_init(c.bar + 8 * (B_SFULL + s), 4); mbar_init(c.bar + 8 * (B_SEMPTY + s), 1); }
    mbar_init(c.bar + 8 * B_AUXA, 1); mbar_init(c.bar + 8 * B_AUXB, 1);
    mbar_init(c.bar + 8 * B_RDY0, 2); mbar_init(c.bar + 8 * B_RDY1, 2); mbar_init(c.bar + 8 * B_SPARE, 2);
    asm volatile("fence.mbarrier_init.release.cluster;" ::: "memory");
  }
  uint32_t ctr;
  asm volatile("ld.relaxed.gpu.global.u32 %0, [%1];" : "=r"(ctr) : "l"(&g_ctr) : "memory");
  asm volatile("barrier.cluster.arrive.release.aligned;\nbarrier.cluster.wait.acquire.aligned;" ::: "memory");
  c.ep1 = (ctr >> 7) + 1;
  if (warp >= 8) {
    asm volatile("setmaxnreg.dec.sync.aligned.u32 88;");
    if (warp == 8) {
      if (lane == 0) { produce_b<0>(p, c); produce_b<1>(p, c); produce_b<2>(p, c); produce_b<3>(p, c); produce_b<4>(p, c); produce_b<5>(p, c); }
    } else if (warp == 9) {
      if (lane == 0) { produce_a<0>(p, c); produce_a<1>(p, c); produce_a<2>(p, c); produce_a<3>(p, c); produce_a<4>(p, c); produce_a<5>(p, c); }
    } else {
      aux_warp(p, c, warp - 10, lane);
    }
    __syncwarp();
  } else {
    asm volatile("setmaxnreg.inc.sync.aligned.u32 208;");
    const int wg = warp >> 2, w = warp & 3, tid = threadIdx.x & 127;
    const bool do_rel = tid < 2;
    const uint32_t rel = mapa(c.bar + 8 * B_EMPTY, tid & 1);
    const int r = lane >> 2, q = lane & 3;
    {
      float acc[96];
      mainloop<0>(acc, c, wg, rel, do_rel);
      epi_attn<0>(acc, c, wg, w, lane);
      if (tid == 0) PROF(wg, 2);
    }
    {
      float acc[96];
      mainloop<1>(acc, c, wg, rel, do_rel);
      epi_attn<1>(acc, c, wg, w, lane);
      if (tid == 0) PROF(wg, 5);
    }
    {
      float acc[64]; uint32_t res[32];
      const bf16* xp = p.x + (size_t)(128 * c.i + 2 * (16 * w + r) + wg) * D_ + 128 * c.j + 2 * q;
#pragma unroll
      for (int t = 0; t < 16; t++) { res[2 * t] = ldcg32(xp + 8 * t); res[2 * t + 1] = ldcg32(xp + 16 * D_ + 8 * t); }
      mainloop<2>(acc, c, wg, rel, do_rel);
      mbar_wait(c.bar + 8 * (B_SEMPTY + wg), 1);
      epi_res(acc, res, 1.f, 1.f, c, wg, w, lane);
      if (tid == 0) PROF(wg, 8);
    }
    {
      float acc[128];
      mainloop<3>(acc, c, wg, rel, do_rel);
      mbar_wait(c.bar + 8 * B_RDY1, 0);
      epi_ffn1<4>(acc, c, wg, w, lane);
      if (tid == 0) PROF(wg, 11);
    }
    {
      float acc[96];
      mainloop<4>(acc, c, wg, rel, do_rel);
      epi_ffn1<3>(acc, c, wg, w, lane);
      if (tid == 0) PROF(wg, 14);
    }
    {
      float acc[64]; uint32_t res[32];
      const bf16* hp = g_h + (size_t)(128 * c.i + 64 * wg + 16 * w + r) * D_ + 128 * c.j + 2 * q;
#pragma unroll
      for (int t = 0; t < 16; t++) { res[2 * t] = ldcg32(hp + 8 * t); res[2 * t + 1] = ldcg32(hp + 8 * D_ + 8 * t); }
      const float sc0 = lds64f(c.sb + OFF_ST + (wg * 64 + w * 16 + r) * 8).y, sc1 = lds64f(c.sb + OFF_ST + (wg * 64 + w * 16 + r + 8) * 8).y;
      mainloop<5>(acc, c, wg, rel, do_rel);
      mbar_wait(c.bar + 8 * (B_SEMPTY + wg), 0);
      epi_res(acc, res, sc0, sc1, c, wg, w, lane);
      if (tid == 0) PROF(wg, 17);
    }
  }
  asm volatile("barrier.cluster.arrive.release.aligned;\nbarrier.cluster.wait.acquire.aligned;" ::: "memory");
  if (threadIdx.x == 0) { atomicAdd(&g_ctr, 1u); PROF(2, 11); }
}

typedef CUresult (*EncFn)(CUtensorMap*, CUtensorMapDataType, cuuint32_t, void*, const cuuint64_t*, const cuuint64_t*, const cuuint32_t*,
                          const cuuint32_t*, CUtensorMapInterleave, CUtensorMapSwizzle, CUtensorMapL2promotion, CUtensorMapFloatOOBfill);

void enc(EncFn f, CUtensorMap* m, const void* ptr, int rank, cuuint64_t d0, cuuint64_t d1, cuuint64_t d2, cuuint64_t s1, cuuint64_t s2,
         cuuint32_t b0, cuuint32_t b1, cuuint32_t b2) {
  const cuuint64_t dims[3] = {d0, d1, d2}, str[2] = {s1, s2};
  const cuuint32_t box[3] = {b0, b1, b2}, es[3] = {1, 1, 1};
  f(m, CU_TENSOR_MAP_DATA_TYPE_BFLOAT16, rank, const_cast<void*>(ptr), dims, str, box, es, CU_TENSOR_MAP_INTERLEAVE_NONE,
    CU_TENSOR_MAP_SWIZZLE_128B, CU_TENSOR_MAP_L2_PROMOTION_L2_256B, CU_TENSOR_MAP_FLOAT_OOB_FILL_NONE);
}

}

extern "C" void kernel_launch(void* const* d_in, const int* in_sizes, int n_in, void* d_out, int out_size) {
  (void)in_sizes; (void)n_in; (void)out_size;
  const void *x = d_in[0], *wqkv = d_in[1], *wo = d_in[2], *w1 = d_in[4], *w2 = d_in[5];
  EncFn f = nullptr;
  cudaDriverEntryPointQueryResult qr;
  cudaGetDriverEntryPoint("cuTensorMapEncodeTiled", (void**)&f, cudaEnableDefault, &qr);
  void *po, *ph, *ph1;
  cudaGetSymbolAddress(&po, g_o); cudaGetSymbolAddress(&ph, g_h); cudaGetSymbolAddress(&ph1, g_h1);
  Params p;
  enc(f, &p.mX, x, 3, D_, 2, S_ / 2, D_ * 2, D_ * 4, 64, 1, 64);
  enc(f, &p.mOut, d_out, 3, D_, 2, S_ / 2, D_ * 2, D_ * 4, 64, 1, 64);
  enc(f, &p.mWqkv, wqkv, 3, D_, D_, 3, 3 * D_ * 2, D_ * 2, 64, 64, 3);
  enc(f, &p.mWo, wo, 3, 64, D_, D_ / 64, D_ * 2, 128, 64, 64, 2);
  enc(f, &p.mW1a, w1, 3, 64, D_, F_ / 64, F_ * 2, 128, 64, 64, 4);
  enc(f, &p.mW1b, w1, 3, 64, D_, F_ / 64, F_ * 2, 128, 64, 64, 3);
  enc(f, &p.mW2, w2, 3, 64, F_, D_ / 64, D_ * 2, 128, 64, 64, 2);
  enc(f, &p.mO, po, 2, D_, S_, 1, D_ * 2, 0, 64, 64, 1);
  enc(f, &p.mH, ph, 2, D_, S_, 1, D_ * 2, 0, 64, 64, 1);
  enc(f, &p.mH1, ph1, 2, F_, S_, 1, F_ * 2, 0, 64, 64, 1);
  p.x = (const bf16*)x;
  for (int cl = 0; cl < 64; cl++) p.role[cl] = (unsigned char)cl;
  cudaFuncSetAttribute(fused_block_kernel, cudaFuncAttributeMaxDynamicSharedMemorySize, SMEM_BYTES);
  fused_block_kernel<<<128, 384, SMEM_BYTES>>>(p);
}
```

```cpp
#include <cuda_runtime.h>
#include <cuda_bf16.h>
#include <cuda.h>
#include <stdint.h>

namespace {

template <int FIRST> __device__ __forceinline__ void wgmma4_n128(float (&d)[64], uint32_t a, uint32_t b) {
#define WGD "{%0, %1, %2, %3, %4, %5, %6, %7, %8, %9, %10, %11, %12, %13, %14, %15, %16, %17, %18, %19, %20, %21, %22, %23, %24, %25, %26, %27, %28, %29, %30, %31, %32, %33, %34, %35, %36, %37, %38, %39, %40, %41, %42, %43, %44, %45, %46, %47, %48, %49, %50, %51, %52, %53, %54, %55, %56, %57, %58, %59, %60, %61, %62, %63}"
  asm volatile("{\n.reg .pred p, q;\n.reg .b64 da, db;\n.reg .b32 x, y;\nsetp.eq.b32 p, %66, 0;\nsetp.eq.b32 q, 0, 0;\n"
    "add.s32 x, %64, 0;\nadd.s32 y, %65, 0;\nmov.b64 da, {x, %67};\nmov.b64 db, {y, %67};\n"
    "wgmma.mma_async.sync.aligned.m64n128k16.f32.bf16.bf16 " WGD ", da, db, p, 1, 1, 0, 1;\n"
    "add.s32 x, %64, 2;\nadd.s32 y, %65, 128;\nmov.b64 da, {x, %67};\nmov.b64 db, {y, %67};\n"
    "wgmma.mma_async.sync.aligned.m64n128k16.f32.bf16.bf16 " WGD ", da, db, q, 1, 1, 0, 1;\n"
    "add.s32 x, %64, 4;\nadd.s32 y, %65, 256;\nmov.b64 da, {x, %67};\nmov.b64 db, {y, %67};\n"
    "wgmma.mma_async.sync.aligned.m64n128k16.f32.bf16.bf16 " WGD ", da, db, q, 1, 1, 0, 1;\n"
    "add.s32 x, %64, 6;\nadd.s32 y, %65, 384;\nmov.b64 da, {x, %67};\nmov.b64 db, {y, %67};\n"
    "wgmma.mma_async.sync.aligned.m64n128k16.f32.bf16.bf16 " WGD ", da, db, q, 1, 1, 0, 1;\n"
    "}\n"
    : "+f"(d[0]), "+f"(d[1]), "+f"(d[2]), "+f"(d[3]), "+f"(d[4]), "+f"(d[5]), "+f"(d[6]), "+f"(d[7]),
      "+f"(d[8]), "+f"(d[9]), "+f"(d[10]), "+f"(d[11]), "+f"(d[12]), "+f"(d[13]), "+f"(d[14]), "+f"(d[15]),
      "+f"(d[16]), "+f"(d[17]), "+f"(d[18]), "+f"(d[19]), "+f"(d[20]), "+f"(d[21]), "+f"(d[22]), "+f"(d[23]),
      "+f"(d[24]), "+f"(d[25]), "+f"(d[26]), "+f"(d[27]), "+f"(d[28]), "+f"(d[29]), "+f"(d[30]), "+f"(d[31]),
      "+f"(d[32]), "+f"(d[33]), "+f"(d[34]), "+f"(d[35]), "+f"(d[36]), "+f"(d[37]), "+f"(d[38]), "+f"(d[39]),
      "+f"(d[40]), "+f"(d[41]), "+f"(d[42]), "+f"(d[43]), "+f"(d[44]), "+f"(d[45]), "+f"(d[46]), "+f"(d[47]),
      "+f"(d[48]), "+f"(d[49]), "+f"(d[50]), "+f"(d[51]), "+f"(d[52]), "+f"(d[53]), "+f"(d[54]), "+f"(d[55]),
      "+f"(d[56]), "+f"(d[57]), "+f"(d[58]), "+f"(d[59]), "+f"(d[60]), "+f"(d[61]), "+f"(d[62]), "+f"(d[63])
    : "r"(a), "r"(b), "n"(FIRST), "r"(0x40000040));
#undef WGD
}

template <int FIRST> __device__ __forceinline__ void wgmma4_n192(float (&d)[96], uint32_t a, uint32_t b) {
#define WGD "{%0, %1, %2, %3, %4, %5, %6, %7, %8, %9, %10, %11, %12, %13, %14, %15, %16, %17, %18, %19, %20, %21, %22, %23, %24, %25, %26, %27, %28, %29, %30, %31, %32, %33, %34, %35, %36, %37, %38, %39, %40, %41, %42, %43, %44, %45, %46, %47, %48, %49, %50, %51, %52, %53, %54, %55, %56, %57, %58, %59, %60, %61, %62, %63, %64, %65, %66, %67, %68, %69, %70, %71, %72, %73, %74, %75, %76, %77, %78, %79, %80, %81, %82, %83, %84, %85, %86, %87, %88, %89, %90, %91, %92, %93, %94, %95}"
  asm volatile("{\n.reg .pred p, q;\n.reg .b64 da, db;\n.reg .b32 x, y;\nsetp.eq.b32 p, %98, 0;\nsetp.eq.b32 q, 0, 0;\n"
    "add.s32 x, %96, 0;\nadd.s32 y, %97, 0;\nmov.b64 da, {x, %99};\nmov.b64 db, {y, %99};\n"
    "wgmma.mma_async.sync.aligned.m64n192k16.f32.bf16.bf16 " WGD ", da, db, p, 1, 1, 0, 1;\n"
    "add.s32 x, %96, 2;\nadd.s32 y, %97, 128;\nmov.b64 da, {x, %99};\nmov.b64 db, {y, %99};\n"
    "wgmma.mma_async.sync.aligned.m64n192k16.f32.bf16.bf16 " WGD ", da, db, q, 1, 1, 0, 1;\n"
    "add.s32 x, %96, 4;\nadd.s32 y, %97, 256;\nmov.b64 da, {x, %99};\nmov.b64 db, {y, %99};\n"
    "wgmma.mma_async.sync.aligned.m64n192k16.f32.bf16.bf16 " WGD ", da, db, q, 1, 1, 0, 1;\n"
    "add.s32 x, %96, 6;\nadd.s32 y, %97, 384;\nmov.b64 da, {x, %99};\nmov.b64 db, {y, %99};\n"
    "wgmma.mma_async.sync.aligned.m64n192k16.f32.bf16.bf16 " WGD ", da, db, q, 1, 1, 0, 1;\n"
    "}\n"
    : "+f"(d[0]), "+f"(d[1]), "+f"(d[2]), "+f"(d[3]), "+f"(d[4]), "+f"(d[5]), "+f"(d[6]), "+f"(d[7]),
      "+f"(d[8]), "+f"(d[9]), "+f"(d[10]), "+f"(d[11]), "+f"(d[12]), "+f"(d[13]), "+f"(d[14]), "+f"(d[15]),
      "+f"(d[16]), "+f"(d[17]), "+f"(d[18]), "+f"(d[19]), "+f"(d[20]), "+f"(d[21]), "+f"(d[22]), "+f"(d[23]),
      "+f"(d[24]), "+f"(d[25]), "+f"(d[26]), "+f"(d[27]), "+f"(d[28]), "+f"(d[29]), "+f"(d[30]), "+f"(d[31]),
      "+f"(d[32]), "+f"(d[33]), "+f"(d[34]), "+f"(d[35]), "+f"(d[36]), "+f"(d[37]), "+f"(d[38]), "+f"(d[39]),
      "+f"(d[40]), "+f"(d[41]), "+f"(d[42]), "+f"(d[43]), "+f"(d[44]), "+f"(d[45]), "+f"(d[46]), "+f"(d[47]),
      "+f"(d[48]), "+f"(d[49]), "+f"(d[50]), "+f"(d[51]), "+f"(d[52]), "+f"(d[53]), "+f"(d[54]), "+f"(d[55]),
      "+f"(d[56]), "+f"(d[57]), "+f"(d[58]), "+f"(d[59]), "+f"(d[60]), "+f"(d[61]), "+f"(d[62]), "+f"(d[63]),
      "+f"(d[64]), "+f"(d[65]), "+f"(d[66]), "+f"(d[67]), "+f"(d[68]), "+f"(d[69]), "+f"(d[70]), "+f"(d[71]),
      "+f"(d[72]), "+f"(d[73]), "+f"(d[74]), "+f"(d[75]), "+f"(d[76]), "+f"(d[77]), "+f"(d[78]), "+f"(d[79]),
      "+f"(d[80]), "+f"(d[81]), "+f"(d[82]), "+f"(d[83]), "+f"(d[84]), "+f"(d[85]), "+f"(d[86]), "+f"(d[87]),
      "+f"(d[88]), "+f"(d[89]), "+f"(d[90]), "+f"(d[91]), "+f"(d[92]), "+f"(d[93]), "+f"(d[94]), "+f"(d[95])
    : "r"(a), "r"(b), "n"(FIRST), "r"(0x40000040));
#undef WGD
}

template <int FIRST> __device__ __forceinline__ void wgmma4_n256(float (&d)[128], uint32_t a, uint32_t b) {
#define WGD "{%0, %1, %2, %3, %4, %5, %6, %7, %8, %9, %10, %11, %12, %13, %14, %15, %16, %17, %18, %19, %20, %21, %22, %23, %24, %25, %26, %27, %28, %29, %30, %31, %32, %33, %34, %35, %36, %37, %38, %39, %40, %41, %42, %43, %44, %45, %46, %47, %48, %49, %50, %51, %52, %53, %54, %55, %56, %57, %58, %59, %60, %61, %62, %63, %64, %65, %66, %67, %68, %69, %70, %71, %72, %73, %74, %75, %76, %77, %78, %79, %80, %81, %82, %83, %84, %85, %86, %87, %88, %89, %90, %91, %92, %93, %94, %95, %96, %97, %98, %99, %100, %101, %102, %103, %104, %105, %106, %107, %108, %109, %110, %111, %112, %113, %114, %115, %116, %117, %118, %119, %120, %121, %122, %123, %124, %125, %126, %127}"
  asm volatile("{\n.reg .pred p, q;\n.reg .b64 da, db;\n.reg .b32 x, y;\nsetp.eq.b32 p, %130, 0;\nsetp.eq.b32 q, 0, 0;\n"
    "add.s32 x, %128, 0;\nadd.s32 y, %129, 0;\nmov.b64 da, {x, %131};\nmov.b64 db, {y, %131};\n"
    "wgmma.mma_async.sync.aligned.m64n256k16.f32.bf16.bf16 " WGD ", da, db, p, 1, 1, 0, 1;\n"
    "add.s32 x, %128, 2;\nadd.s32 y, %129, 128;\nmov.b64 da, {x, %131};\nmov.b64 db, {y, %131};\n"
    "wgmma.mma_async.sync.aligned.m64n256k16.f32.bf16.bf16 " WGD ", da, db, q, 1, 1, 0, 1;\n"
    "add.s32 x, %128, 4;\nadd.s32 y, %129, 256;\nmov.b64 da, {x, %131};\nmov.b64 db, {y, %131};\n"
    "wgmma.mma_async.sync.aligned.m64n256k16.f32.bf16.bf16 " WGD ", da, db, q, 1, 1, 0, 1;\n"
    "add.s32 x, %128, 6;\nadd.s32 y, %129, 384;\nmov.b64 da, {x, %131};\nmov.b64 db, {y, %131};\n"
    "wgmma.mma_async.sync.aligned.m64n256k16.f32.bf16.bf16 " WGD ", da, db, q, 1, 1, 0, 1;\n"
    "}\n"
    : "+f"(d[0]), "+f"(d[1]), "+f"(d[2]), "+f"(d[3]), "+f"(d[4]), "+f"(d[5]), "+f"(d[6]), "+f"(d[7]),
      "+f"(d[8]), "+f"(d[9]), "+f"(d[10]), "+f"(d[11]), "+f"(d[12]), "+f"(d[13]), "+f"(d[14]), "+f"(d[15]),
      "+f"(d[16]), "+f"(d[17]), "+f"(d[18]), "+f"(d[19]), "+f"(d[20]), "+f"(d[21]), "+f"(d[22]), "+f"(d[23]),
      "+f"(d[24]), "+f"(d[25]), "+f"(d[26]), "+f"(d[27]), "+f"(d[28]), "+f"(d[29]), "+f"(d[30]), "+f"(d[31]),
      "+f"(d[32]), "+f"(d[33]), "+f"(d[34]), "+f"(d[35]), "+f"(d[36]), "+f"(d[37]), "+f"(d[38]), "+f"(d[39]),
      "+f"(d[40]), "+f"(d[41]), "+f"(d[42]), "+f"(d[43]), "+f"(d[44]), "+f"(d[45]), "+f"(d[46]), "+f"(d[47]),
      "+f"(d[48]), "+f"(d[49]), "+f"(d[50]), "+f"(d[51]), "+f"(d[52]), "+f"(d[53]), "+f"(d[54]), "+f"(d[55]),
      "+f"(d[56]), "+f"(d[57]), "+f"(d[58]), "+f"(d[59]), "+f"(d[60]), "+f"(d[61]), "+f"(d[62]), "+f"(d[63]),
      "+f"(d[64]), "+f"(d[65]), "+f"(d[66]), "+f"(d[67]), "+f"(d[68]), "+f"(d[69]), "+f"(d[70]), "+f"(d[71]),
      "+f"(d[72]), "+f"(d[73]), "+f"(d[74]), "+f"(d[75]), "+f"(d[76]), "+f"(d[77]), "+f"(d[78]), "+f"(d[79]),
      "+f"(d[80]), "+f"(d[81]), "+f"(d[82]), "+f"(d[83]), "+f"(d[84]), "+f"(d[85]), "+f"(d[86]), "+f"(d[87]),
      "+f"(d[88]), "+f"(d[89]), "+f"(d[90]), "+f"(d[91]), "+f"(d[92]), "+f"(d[93]), "+f"(d[94]), "+f"(d[95]),
      "+f"(d[96]), "+f"(d[97]), "+f"(d[98]), "+f"(d[99]), "+f"(d[100]), "+f"(d[101]), "+f"(d[102]), "+f"(d[103]),
      "+f"(d[104]), "+f"(d[105]), "+f"(d[106]), "+f"(d[107]), "+f"(d[108]), "+f"(d[109]), "+f"(d[110]), "+f"(d[111]),
      "+f"(d[112]), "+f"(d[113]), "+f"(d[114]), "+f"(d[115]), "+f"(d[116]), "+f"(d[117]), "+f"(d[118]), "+f"(d[119]),
      "+f"(d[120]), "+f"(d[121]), "+f"(d[122]), "+f"(d[123]), "+f"(d[124]), "+f"(d[125]), "+f"(d[126]), "+f"(d[127])
    : "r"(a), "r"(b), "n"(FIRST), "r"(0x40000040));
#undef WGD
}

#define AUX_GATE 5
#define XLD_EARLY 0
#define XST 6
#define RELFLAG 1
#define PF_Q 9
#define PF_W1 12
#define LAYOUT 3
typedef __nv_bfloat16 bf16;
constexpr int S_ = 2048, D_ = 1024, F_ = 3584;
constexpr int OFF_SPARE = 160 * 1024, OFF_STG = 192 * 1024, OFF_CS = 224 * 1024, OFF_ST = OFF_CS + 1792, OFF_BAR = OFF_ST + 1024;
constexpr int SMEM_BYTES = 232448;
constexpr uint32_t SMEM_BASE = 1024;
enum { B_FULL = 0, B_EMPTY = 8, B_SFULL = 16, B_SFA = 18, B_HALO = 20, B_RDY0 = 22, B_RDY1 = 23, B_SEMPTY = 24, B_AUX = 26, B_NUM = 28 };
enum { F_O = 0, F_H = 64, F_H1 = 96, F_NUM = 160 };

struct Params {
  CUtensorMap mX, mWkv, mWq, mCq, mC1, mWo, mW1a, mW1b, mW2, mO, mH, mH1, mOut;
  const bf16* x;
};

__device__ __align__(1024) bf16 g_o[S_ * D_];
__device__ __align__(1024) bf16 g_h[S_ * D_];
__device__ __align__(1024) bf16 g_h1[S_ * F_];
__device__ __align__(128) float2 g_xst[S_];
__device__ __align__(128) float2 g_hst[S_ * 8];
__device__ __align__(128) float g_cs[8 * 8 * 832];
__device__ __align__(128) uint4 g_halo[16 * 8 * 2 * 2 * 256];
__device__ __align__(128) uint32_t g_flag[F_NUM * 8];
__device__ uint32_t g_ctr;
#define PROF(idx) do {} while (0)

constexpr int SPIN_LIMIT = 1 << 22;

__device__ __forceinline__ void mbar_init(uint32_t bar, uint32_t cnt) { asm volatile("mbarrier.init.shared::cta.b64 [%0], %1;" ::"r"(bar), "r"(cnt)); }
__device__ __forceinline__ void mbar_expect_tx(uint32_t bar, uint32_t bytes) { asm volatile("mbarrier.arrive.expect_tx.shared::cta.b64 _, [%0], %1;" ::"r"(bar), "r"(bytes) : "memory"); }
__device__ __forceinline__ void mbar_arrive(uint32_t bar) { asm volatile("mbarrier.arrive.shared::cta.b64 _, [%0];" ::"r"(bar) : "memory"); }
__device__ __forceinline__ void mbar_arrive_cl(uint32_t bar_cluster_addr) { asm volatile("mbarrier.arrive.shared::cluster.b64 _, [%0];" ::"r"(bar_cluster_addr) : "memory"); }
__device__ __forceinline__ uint32_t mapa(uint32_t a, uint32_t cta) { uint32_t r; asm("mapa.shared::cluster.u32 %0, %1, %2;" : "=r"(r) : "r"(a), "r"(cta)); return r; }
__device__ __forceinline__ void spin_check(int& it) { asm volatile("{\n.reg .pred p;\nsetp.gt.s32 p, %0, %1;\n@p trap;\n}\n" ::"r"(++it), "n"(SPIN_LIMIT)); }
__device__ __forceinline__ void mbar_wait(uint32_t bar, uint32_t parity) {
  asm volatile("{\n.reg .pred p;\n.reg .s32 n;\nmov.s32 n, 0;\n"
               "W: mbarrier.try_wait.parity.shared::cta.b64 p, [%0], %1;\n@p bra D;\n"
               "add.s32 n, n, 1;\nsetp.lt.s32 p, n, %2;\n@p bra W;\ntrap;\nD:\n}\n" ::"r"(bar), "r"(parity), "n"(SPIN_LIMIT) : "memory");
}
__device__ __forceinline__ void mbar_wait_u(uint32_t bar, uint32_t parity, int& n) {
  asm volatile("{\n.reg .pred p;\n"
               "W: mbarrier.try_wait.parity.shared::cta.b64 p, [%1], %2;\n@!p add.s32 %0, %0, 1;\n"
               "setp.lt.and.s32 p, %0, %3, !p;\n@p bra.uni W;\n}\n" : "+r"(n) : "r"(bar), "r"(parity), "n"(SPIN_LIMIT) : "memory");
}
__device__ __forceinline__ void flag_add(int f) {
  if (RELFLAG) asm volatile("red.relaxed.gpu.global.add.u32 [%0], 1;" ::"l"(g_flag + f * 8) : "memory");
  else asm volatile("red.release.gpu.global.add.u32 [%0], 1;" ::"l"(g_flag + f * 8) : "memory");
}
__device__ __forceinline__ void flag_wait(int f, uint32_t target) {
  uint32_t v; int it = 0;
  do {
    asm volatile("ld.acquire.gpu.global.u32 %0, [%1];" : "=r"(v) : "l"(g_flag + f * 8) : "memory");
    spin_check(it);
  } while ((int)(v - target) < 0);
}
__device__ __forceinline__ void fence_async_global() { asm volatile("fence.proxy.async.global;" ::: "memory"); }
__device__ __forceinline__ void fence_async_smem() { asm volatile("fence.proxy.async.shared::cta;" ::: "memory"); }
__device__ __forceinline__ void tma2d(uint32_t dst, const CUtensorMap* m, uint32_t bar, int c0, int c1) {
  asm volatile("cp.async.bulk.tensor.2d.shared::cluster.global.mbarrier::complete_tx::bytes [%0], [%1, {%3, %4}], [%2];"
               ::"r"(dst), "l"(m), "r"(bar), "r"(c0), "r"(c1) : "memory");
}
__device__ __forceinline__ void bulk_s2s(uint32_t dst_cl, uint32_t src, uint32_t bytes, uint32_t bar_cl) {
  asm volatile("cp.async.bulk.shared::cluster.shared::cta.mbarrier::complete_tx::bytes [%0], [%1], %2, [%3];" ::"r"(dst_cl), "r"(src), "r"(bytes), "r"(bar_cl) : "memory");
}
__device__ __forceinline__ void map_prefetch(const CUtensorMap* m) { asm volatile("prefetch.tensormap [%0];" ::"l"(m) : "memory"); }
__device__ __forceinline__ void tma2d_mc(uint32_t dst, const CUtensorMap* m, uint32_t bar, int c0, int c1) {
  asm volatile("cp.async.bulk.tensor.2d.shared::cluster.global.mbarrier::complete_tx::bytes.multicast::cluster [%0], [%1, {%3, %4}], [%2], %5;"
               ::"r"(dst), "l"(m), "r"(bar), "r"(c0), "r"(c1), "h"((uint16_t)3) : "memory");
}
__device__ __forceinline__ void tma3d(uint32_t dst, const CUtensorMap* m, uint32_t bar, int c0, int c1, int c2) {
  asm volatile("cp.async.bulk.tensor.3d.shared::cluster.global.mbarrier::complete_tx::bytes [%0], [%1, {%3, %4, %5}], [%2];"
               ::"r"(dst), "l"(m), "r"(bar), "r"(c0), "r"(c1), "r"(c2) : "memory");
}
__device__ __forceinline__ void tma4d(uint32_t dst, const CUtensorMap* m, uint32_t bar, int c0, int c1, int c2, int c3) {
  asm volatile("cp.async.bulk.tensor.4d.shared::cluster.global.mbarrier::complete_tx::bytes [%0], [%1, {%3, %4, %5, %6}], [%2];"
               ::"r"(dst), "l"(m), "r"(bar), "r"(c0), "r"(c1), "r"(c2), "r"(c3) : "memory");
}
__device__ __forceinline__ void tma3d_mc(uint32_t dst, const CUtensorMap* m, uint32_t bar, int c0, int c1, int c2) {
  asm volatile("cp.async.bulk.tensor.3d.shared::cluster.global.mbarrier::complete_tx::bytes.multicast::cluster [%0], [%1, {%3, %4, %5}], [%2], %6;"
               ::"r"(dst), "l"(m), "r"(bar), "r"(c0), "r"(c1), "r"(c2), "h"((uint16_t)3) : "memory");
}
__device__ __forceinline__ void tma3d_prefetch(const CUtensorMap* m, int c0, int c1, int c2) {
  asm volatile("cp.async.bulk.prefetch.tensor.3d.L2.global [%0, {%1, %2, %3}];" ::"l"(m), "r"(c0), "r"(c1), "r"(c2) : "memory");
}
__device__ __forceinline__ void tma2d_st(const CUtensorMap* m, uint32_t src, int c0, int c1) {
  asm volatile("cp.async.bulk.tensor.2d.global.shared::cta.bulk_group [%0, {%2, %3}], [%1];" ::"l"(m), "r"(src), "r"(c0), "r"(c1) : "memory");
}
__device__ __forceinline__ void tma3d_st(const CUtensorMap* m, uint32_t src, int c0, int c1, int c2) {
  asm volatile("cp.async.bulk.tensor.3d.global.shared::cta.bulk_group [%0, {%2, %3, %4}], [%1];" ::"l"(m), "r"(src), "r"(c0), "r"(c1), "r"(c2) : "memory");
}
__device__ __forceinline__ void bulk_commit() { asm volatile("cp.async.bulk.commit_group;" ::: "memory"); }
__device__ __forceinline__ void bulk_wait_read() { asm volatile("cp.async.bulk.wait_group.read 0;" ::: "memory"); }
__device__ __forceinline__ void bulk_wait_all() { asm volatile("cp.async.bulk.wait_group 0;" ::: "memory"); }
__device__ __forceinline__ void wg_fence() { asm volatile("wgmma.fence.sync.aligned;" ::: "memory"); }
__device__ __forceinline__ void wg_commit() { asm volatile("wgmma.commit_group.sync.aligned;" ::: "memory"); }
template <int N> __device__ __forceinline__ void wg_wait() { asm volatile("wgmma.wait_group.sync.aligned %0;" ::"n"(N) : "memory"); }
__device__ __forceinline__ void named_sync(int id, int n) { asm volatile("bar.sync %0, %1;" ::"r"(id), "r"(n) : "memory"); }
__device__ __forceinline__ uint32_t pack2(float lo, float hi) { uint32_t r; asm("cvt.rn.bf16x2.f32 %0, %1, %2;" : "=r"(r) : "f"(hi), "f"(lo)); return r; }
__device__ __forceinline__ uint32_t pack2_relu(float lo, float hi) { uint32_t r; asm("cvt.rn.relu.bf16x2.f32 %0, %1, %2;" : "=r"(r) : "f"(hi), "f"(lo)); return r; }
__device__ __forceinline__ float ex2(float x) { float r; asm("ex2.approx.ftz.f32 %0, %1;" : "=f"(r) : "f"(x)); return r; }
__device__ __forceinline__ float rcp(float x) { float r; asm("rcp.approx.ftz.f32 %0, %1;" : "=f"(r) : "f"(x)); return r; }
__device__ __forceinline__ float bf_lo(uint32_t v) { return __uint_as_float(v << 16); }
__device__ __forceinline__ float bf_hi(uint32_t v) { return __uint_as_float(v & 0xFFFF0000u); }
__device__ __forceinline__ uint4 ldcg128(const void* p) { uint4 v; asm volatile("ld.global.cg.v4.b32 {%0, %1, %2, %3}, [%4];" : "=r"(v.x), "=r"(v.y), "=r"(v.z), "=r"(v.w) : "l"(p)); return v; }
__device__ __forceinline__ void stsm4(uint32_t a, uint32_t r0, uint32_t r1, uint32_t r2, uint32_t r3) {
  asm volatile("stmatrix.sync.aligned.m8n8.x4.shared.b16 [%0], {%1, %2, %3, %4};" ::"r"(a), "r"(r0), "r"(r1), "r"(r2), "r"(r3) : "memory");
}
__device__ __forceinline__ void ldsm4(uint32_t a, uint32_t& r0, uint32_t& r1, uint32_t& r2, uint32_t& r3) {
  asm volatile("ldmatrix.sync.aligned.m8n8.x4.shared.b16 {%0, %1, %2, %3}, [%4];" : "=r"(r0), "=r"(r1), "=r"(r2), "=r"(r3) : "r"(a) : "memory");
}
__device__ __forceinline__ uint32_t movm(uint32_t a) { uint32_t d; asm volatile("movmatrix.sync.aligned.m8n8.trans.b16 %0, %1;" : "=r"(d) : "r"(a)); return d; }
__device__ __forceinline__ void mma16(float (&c)[4], uint32_t a0, uint32_t a1, uint32_t a2, uint32_t a3, uint32_t b0, uint32_t b1) {
  asm volatile("mma.sync.aligned.m16n8k16.row.col.f32.bf16.bf16.f32 {%0,%1,%2,%3}, {%4,%5,%6,%7}, {%8,%9}, {%0,%1,%2,%3};"
               : "+f"(c[0]), "+f"(c[1]), "+f"(c[2]), "+f"(c[3]) : "r"(a0), "r"(a1), "r"(a2), "r"(a3), "r"(b0), "r"(b1));
}
__device__ __forceinline__ void mma8(float (&c)[4], uint32_t a0, uint32_t a1, uint32_t b0) {
  asm volatile("mma.sync.aligned.m16n8k8.row.col.f32.bf16.bf16.f32 {%0,%1,%2,%3}, {%4,%5}, {%6}, {%0,%1,%2,%3};"
               : "+f"(c[0]), "+f"(c[1]), "+f"(c[2]), "+f"(c[3]) : "r"(a0), "r"(a1), "r"(b0));
}
__device__ __forceinline__ float2 lds64f(uint32_t a) { float2 v; asm volatile("ld.shared.v2.f32 {%0, %1}, [%2];" : "=f"(v.x), "=f"(v.y) : "r"(a)); return v; }
__device__ __forceinline__ uint4 lds128(uint32_t a) { uint4 v; asm volatile("ld.shared.v4.b32 {%0, %1, %2, %3}, [%4];" : "=r"(v.x), "=r"(v.y), "=r"(v.z), "=r"(v.w) : "r"(a)); return v; }
__device__ __forceinline__ void sts128(uint32_t a, uint32_t x, uint32_t y, uint32_t z, uint32_t w) { asm volatile("st.shared.v4.b32 [%0], {%1, %2, %3, %4};" ::"r"(a), "r"(x), "r"(y), "r"(z), "r"(w) : "memory"); }
__device__ __forceinline__ void sts64f(uint32_t a, float x, float y) { asm volatile("st.shared.v2.f32 [%0], {%1, %2};" ::"r"(a), "f"(x), "f"(y) : "memory"); }
__device__ __forceinline__ float4 lds128f(uint32_t a) { float4 v; asm volatile("ld.shared.v4.f32 {%0, %1, %2, %3}, [%4];" : "=f"(v.x), "=f"(v.y), "=f"(v.z), "=f"(v.w) : "r"(a)); return v; }
__device__ __forceinline__ float lds_bf16(uint32_t a) { uint16_t v; asm volatile("ld.shared.u16 %0, [%1];" : "=h"(v) : "r"(a)); return __uint_as_float((uint32_t)v << 16); }
__device__ __forceinline__ void st_tag2(void* p, float x, float y, uint32_t tag) {
  asm volatile("st.relaxed.gpu.global.v2.b32 [%0], {%1, %2};" ::"l"(p), "r"((__float_as_uint(x) & ~3u) | tag), "r"((__float_as_uint(y) & ~3u) | tag) : "memory");
}
__device__ __forceinline__ float4 ld_tag4(const void* p) { float4 v; asm volatile("ld.relaxed.gpu.global.v4.f32 {%0, %1, %2, %3}, [%4];" : "=f"(v.x), "=f"(v.y), "=f"(v.z), "=f"(v.w) : "l"(p) : "memory"); return v; }
__device__ __forceinline__ uint32_t tag_bad(const float4& v, uint32_t tag) {
  return ((__float_as_uint(v.x) ^ tag) | (__float_as_uint(v.y) ^ tag) | (__float_as_uint(v.z) ^ tag) | (__float_as_uint(v.w) ^ tag)) & 3u;
}

template <int F> __device__ __forceinline__ void wgmma4(float (&d)[64], uint32_t a, uint32_t b) { wgmma4_n128<F>(d, a, b); }
template <int F> __device__ __forceinline__ void wgmma4(float (&d)[96], uint32_t a, uint32_t b) { wgmma4_n192<F>(d, a, b); }
template <int F> __device__ __forceinline__ void wgmma4(float (&d)[128], uint32_t a, uint32_t b) { wgmma4_n256<F>(d, a, b); }

struct Ctx { uint32_t sb, bar, ep1; int i, j, rank; };
template <int PH> struct Geo {
  static constexpr int N0 = PH * 16;
  static constexpr int NS = PH == 5 ? 56 : 16;
  static constexpr int NCH = (PH == 0 || PH == 3) ? 4 : (PH == 4 ? 3 : 2);
  static constexpr int SB = 16384 + NCH * 8192;
  static constexpr int DEPTH = NCH == 2 ? 6 : 4;
  static constexpr int SLOT0 = PH == 0 ? 1 : PH == 1 ? 2 : PH == 3 ? 3 : 0;
  static __device__ __forceinline__ int dep(int m) {
    if (m >= DEPTH || PH == 0 || PH == 2) return N0 + m - DEPTH;
    if (PH == 1) return m == 0 ? 12 : 13 + (m >> 1);
    if (PH == 3) return m == 0 ? N0 - 5 : N0 - 4 + m;
    if (PH == 4) return N0 - 3 + (m < 2 ? m : 2);
    return N0 - 4 + (m < 3 ? m : 3);
  }
  static __device__ __forceinline__ bool own(int m) { return (PH == 2 || PH == 3) && m < 2; }
  static __device__ __forceinline__ bool local(int m) { return (PH == 2 || PH == 3) && m < 4; }
  static __device__ __forceinline__ int koff(int m, int j) {
    if (local(m)) return (128 * j) ^ (64 * m);
    if (PH == 2) { const int t = m < 10 ? m - 4 : m - 10; return 128 * (t < (j & 6) ? t : t + 2) + (m < 10 ? 0 : 64); }
    if (PH == 3) return 64 * (m - 4 < 2 * (j & 6) ? m - 4 : m);
    if (PH == 5) return m < 32 ? 448 * (m >> 2) + 64 * (m & 3) : 448 * ((m - 32) / 3) + 256 + 64 * ((m - 32) % 3);
    return 64 * m;
  }
};
__device__ __forceinline__ void wait_empty(const Ctx& c, int d) { mbar_wait(c.bar + 8 * (B_EMPTY + (d & 7)), (d >> 3) & 1); }

template <int PH> __device__ __forceinline__ void produce_b(const Params& p, const Ctx& c, int m0, int m1) {
  using G = Geo<PH>;
  int slot = G::SLOT0;
#pragma unroll 1
  for (int m = m0; m < m1; m++) {
    const int n = G::N0 + m, d = G::dep(m);
    if (d >= 0) wait_empty(c, d);
    if (PH == 5 && m == 5) { mbar_wait(c.bar + 8 * B_SEMPTY, 1); mbar_wait(c.bar + 8 * (B_SEMPTY + 1), 1); }
    const uint32_t fb = c.bar + 8 * (n & 7), dst = c.sb + slot * G::SB + 16384;
    mbar_expect_tx(fb, G::own(m) ? G::SB - 16384 : G::SB);
    const int k0 = G::koff(m, c.j);
    if (PH == 0) tma4d(dst, &p.mWkv, fb, 0, k0, 2 * c.j, 1);
    if (PH == 1) tma3d(dst, &p.mWq, fb, 0, k0, 2 * c.j);
    if (PH == 2) tma3d(dst, &p.mWo, fb, 0, k0, 2 * c.j);
    if (PH == 3) tma3d(dst, &p.mW1a, fb, 0, k0, 7 * c.j);
    if (PH == 4) tma3d(dst, &p.mW1b, fb, 0, k0, 7 * c.j + 4);
    if (PH == 5) tma3d(dst, &p.mW2, fb, 0, k0, 2 * c.j);
    if (PH == 0 && m == 0) PROF(2);
    if (PH == 0 && m == PF_Q) tma3d_prefetch(&p.mWq, 0, 64 * c.i, 2 * c.j);
    if (PH == 0 && m == PF_W1) tma3d_prefetch(&p.mW1a, 0, 64 * c.i, 7 * c.j);
    if (PH == 1 && m == 0) tma3d_prefetch(&p.mWo, 0, 64 * c.i, 2 * c.j);
    if (PH == 1 && m == 8) tma3d_prefetch(&p.mW1b, 0, 64 * c.i, 7 * c.j + 4);
    if (PH == 3 && (m & 3) == 3 && c.i + 4 * (m & 12) < 56) tma3d_prefetch(&p.mW2, 0, Geo<5>::koff(c.i + 4 * (m & 12), 0), 2 * c.j);
    if (++slot == G::DEPTH) slot = 0;
  }
}
template <int PH> __device__ __forceinline__ void produce_a(const Params& p, const Ctx& c) {
  using G = Geo<PH>;
  int slot = G::SLOT0;
  const int row = 128 * c.i + 64 * c.rank;
#pragma unroll 1
  for (int m = 0; m < G::NS; m++) {
    if (!G::local(m)) {
      const int n = G::N0 + m, d = G::dep(m);
      if (PH == 2 && (m == 4 || m == 10)) { flag_wait(F_O + (c.i * 2 + (m >> 3)) * 2 + c.rank, 8 * c.ep1); fence_async_global(); PROF(24 + (m >> 3)); }
      if (PH == 3 && m == 4) { flag_wait(F_H + c.i * 2 + c.rank, 8 * c.ep1); fence_async_global(); PROF(26); }
      if (PH == 5 && (m & 31) == 0) { flag_wait(F_H1 + (c.i * 2 + (m >> 5)) * 2 + c.rank, 8 * c.ep1); fence_async_global(); PROF(27 + (m >> 5)); }
      if (d >= 0) wait_empty(c, d);
      const uint32_t fb = c.bar + 8 * (n & 7), dst = c.sb + slot * G::SB + c.rank * 8192;
      const int k0 = G::koff(m, c.j);
      if (PH <= 1) tma3d_mc(dst, &p.mX, fb, k0, c.rank, 64 * c.i);
      if (PH == 2) tma2d_mc(dst, &p.mO, fb, k0, row);
      if (PH == 3 || PH == 4) tma2d_mc(dst, &p.mH, fb, k0, row);
      if (PH == 5) tma2d_mc(dst, &p.mH1, fb, k0, row);
      if (PH == 0 && m == 0) PROF(3);
    }
    if (++slot == G::DEPTH) slot = 0;
  }
}

struct Con { uint32_t rel, stg, da; int wg, w, lane, spin; bool do_rel; };
template <int PH, bool FIRST> __device__ __forceinline__ void issue(float (&acc)[Geo<PH>::NCH * 32], const Ctx& c, Con& k, int m, int slot) {
  using G = Geo<PH>;
  const int n = G::N0 + m;
  mbar_wait_u(c.bar + 8 * (n & 7), (n >> 3) & 1, k.spin);
  if (m == 0 && k.do_rel) PROF(32 + 32 * k.wg + 3 * PH);
  if (PH == 2 && (m == 4 || m == 10) && k.do_rel) PROF(32 + 32 * k.wg + 19 + (m >> 3));
  if (PH == 3 && (m == 2 || m == 4) && k.do_rel) PROF(32 + 32 * k.wg + 20 + (m >> 1));
  const uint32_t so = slot * (G::SB >> 4);
  wg_fence();
  wgmma4<FIRST>(acc, G::own(m) ? k.da + k.wg * 512 + ((OFF_STG + (m & 1) * 8192) >> 4) : k.da + so, so + (((SMEM_BASE + 16384) >> 4) | (512u << 16)));
  wg_commit();
}
template <int PH> __device__ __forceinline__ void retire(Con& k, int m) {
  wg_wait<1>();
  if (k.do_rel && (PH < 5 || m <= 50)) mbar_arrive_cl(k.rel + 8 * ((Geo<PH>::N0 + m - 1) & 7));
}
template <int PH> __device__ __forceinline__ void finish(Con& k) {
  wg_wait<0>();
  if (PH < 5 && k.do_rel) mbar_arrive_cl(k.rel + 8 * 7);
  if (k.do_rel) PROF(32 + 32 * k.wg + 3 * PH + 1);
}
template <int PH> __device__ __forceinline__ void steps(float (&acc)[Geo<PH>::NCH * 32], const Ctx& c, Con& k, int m0, int m1) {
  using G = Geo<PH>;
  int slot = (G::SLOT0 + m0) % G::DEPTH;
#pragma unroll 1
  for (int m = m0; m < m1; m++) {
    issue<PH, false>(acc, c, k, m, slot);
    if (PH == 4 && m == 8) mbar_wait_u(c.bar + 8 * (B_SEMPTY + k.wg), 0, k.spin);
    retire<PH>(k, m);
    if (++slot == G::DEPTH) slot = 0;
  }
}
#define ISSUE(PH, acc, m) issue<PH, false>(acc, c, k, m, (Geo<PH>::SLOT0 + (m)) % Geo<PH>::DEPTH)
#define ISSUE0(PH, acc) issue<PH, true>(acc, c, k, 0, Geo<PH>::SLOT0)

__device__ __forceinline__ void handoff(const Ctx& c, Con& k, int bar = B_SFULL) {
  fence_async_smem();
  __syncwarp();
  if (k.lane == 0) mbar_arrive(c.bar + 8 * (bar + k.wg));
}

struct Pre { float4 cs[4]; float2 s0, s1; };
template <int PH> __device__ __forceinline__ void pre_load(Pre& a, const Ctx& c, Con& k) {
  if (PH == 0) mbar_wait_u(c.bar + 8 * B_RDY0, 0, k.spin);
  if (PH == 1) { mbar_wait_u(c.bar + 8 * B_RDY1, 0, k.spin); mbar_wait_u(c.bar + 8 * (B_HALO + k.wg), 0, k.spin); }
  if (PH == 4) mbar_wait_u(c.bar + 8 * B_RDY1, 1, k.spin);
  if (PH == 3) { mbar_wait_u(c.bar + 8 * B_RDY0, 1, k.spin); mbar_wait_u(c.bar + 8 * (B_EMPTY + 4), 1, k.spin); }
  const uint32_t sta = c.sb + OFF_ST + (k.wg * 64 + k.w * 16 + (k.lane >> 2)) * 8;
  a.s0 = lds64f(sta); a.s1 = lds64f(sta + 64);
  a.s0.x = -a.s0.x; a.s1.x = -a.s1.x;
#pragma unroll
  for (int u = 0; u < 4; u++) a.cs[u] = lds128f(c.sb + OFF_CS + (Geo<PH>::NCH == 4 ? 0 : 1024) + u * 64 + (k.lane & 3) * 16);
}
template <int PH, int U0, int U1> __device__ __forceinline__ void qkv_pack(uint32_t (&pk)[Geo<PH>::NCH * 8][2], const float (&acc)[Geo<PH>::NCH * 32], Pre& a, const Ctx& c, Con& k) {
  const uint32_t csa = c.sb + OFF_CS + PH * 1024 + (k.lane & 3) * 16;
#pragma unroll
  for (int u = U0; u < U1; u++) {
    const float4 s = a.cs[u & 3];
    if (u + 4 < Geo<PH>::NCH * 4) a.cs[u & 3] = lds128f(csa + (u + 4) * 64);
    float v[8];
#pragma unroll
    for (int e = 0; e < 8; e++) {
      v[e] = fmaf((e & 2) ? a.s1.x : a.s0.x, (e & 4) ? ((e & 1) ? s.w : s.z) : ((e & 1) ? s.y : s.x), acc[8 * u + e]);
      if (PH == 0) v[e] *= (e & 2) ? a.s1.y : a.s0.y;
    }
#pragma unroll
    for (int e = 0; e < 4; e++) pk[2 * u + (e >> 1)][e & 1] = pack2(v[2 * e], v[2 * e + 1]);
  }
}
#define HALO_SRC(kv, H, x) kv[((x) < 8 ? 0 : 8) + 8 * (H) + (x)][1]
__device__ __forceinline__ void halo_publish(uint32_t (&kv)[32][2], const Ctx& c, Con& k) {
#pragma unroll
  for (int t = 16; t < 32; t++) kv[t][1] = movm(kv[t][1]);
  if (k.w < 3) {
    const uint32_t ha = k.stg + (k.w + 1) * 2048 + k.lane * 16;
#pragma unroll
    for (int u = 0; u < 8; u++)
      sts128(ha + (u >> 2) * 8192 + (u & 3) * 512, HALO_SRC(kv, u >> 2, 4 * (u & 3)), HALO_SRC(kv, u >> 2, 4 * (u & 3) + 1), HALO_SRC(kv, u >> 2, 4 * (u & 3) + 2), HALO_SRC(kv, u >> 2, 4 * (u & 3) + 3));
    __syncwarp();
    if (k.lane == 0) mbar_arrive(c.bar + 8 * (B_HALO + k.wg));
  } else if (c.i < 15) {
    uint4* hp = g_halo + ((c.i * 8 + c.j) * 2 + k.wg) * 512 + k.lane;
#pragma unroll
    for (int u = 0; u < 16; u++) {
      const unsigned long long x = ((unsigned long long)c.ep1 << 32) | HALO_SRC(kv, u >> 3, 2 * (u & 7)), y = ((unsigned long long)c.ep1 << 32) | HALO_SRC(kv, u >> 3, 2 * (u & 7) + 1);
      asm volatile("st.relaxed.gpu.global.v2.b64 [%0], {%1, %2};" ::"l"(hp + u * 32), "l"(x), "l"(y) : "memory");
    }
  }
}
template <int H> __device__ __forceinline__ void attend(const uint32_t (&q)[16][2], const uint32_t (&kv)[32][2], float sc0, float sc1, const Ctx& c, Con& k) {
  uint32_t hl[16];
#pragma unroll
  for (int u = 0; u < 4; u++) { const uint4 v = lds128(k.stg + H * 8192 + k.w * 2048 + k.lane * 16 + u * 512); hl[4 * u] = v.x; hl[4 * u + 1] = v.y; hl[4 * u + 2] = v.z; hl[4 * u + 3] = v.w; }
  const bool g0 = 2 * (k.lane & 3) > (k.lane >> 2), g1 = 2 * (k.lane & 3) + 1 > (k.lane >> 2), nohalo = (k.w == 0 && c.i == 0);
  const float L2E = 1.4426950408889634f;
  float sa[2][4], sb[2][4], sh[2][4];
#pragma unroll
  for (int e = 0; e < 8; e++) { sa[e >> 2][e & 3] = 0.f; sb[e >> 2][e & 3] = 0.f; sh[e >> 2][e & 3] = 0.f; }
#pragma unroll
  for (int ks = 0; ks < 2; ks++)
#pragma unroll
    for (int hd = 0; hd < 2; hd++) {
      const int x = 4 * hd + 2 * ks, t = 8 * H + x;
      mma16(sa[hd], q[t][0], q[t][1], q[t + 1][0], q[t + 1][1], kv[t][0], kv[t + 1][0]);
      mma16(sb[hd], q[t][0], q[t][1], q[t + 1][0], q[t + 1][1], kv[t][1], kv[t + 1][1]);
      mma16(sh[hd], q[t][0], q[t][1], q[t + 1][0], q[t + 1][1], hl[x], hl[x + 1]);
    }
  float l[4][2], dn[4]; uint32_t pp[4][2];
#pragma unroll
  for (int hd = 0; hd < 2; hd++) {
    l[2 * hd][0] = (g0 ? sh[hd][0] : sa[hd][0]) * sc0; l[2 * hd][1] = (g1 ? sh[hd][1] : sa[hd][1]) * sc0;
    l[2 * hd + 1][0] = (g0 ? sa[hd][2] : sb[hd][2]) * sc1; l[2 * hd + 1][1] = (g1 ? sa[hd][3] : sb[hd][3]) * sc1;
    if (nohalo && g0) l[2 * hd][0] = -1e9f;
    if (nohalo && g1) l[2 * hd][1] = -1e9f;
  }
#pragma unroll
  for (int e = 0; e < 4; e++) dn[e] = fmaxf(l[e][0], l[e][1]);
#pragma unroll
  for (int o = 1; o < 3; o++)
#pragma unroll
    for (int e = 0; e < 4; e++) dn[e] = fmaxf(dn[e], __shfl_xor_sync(~0u, dn[e], o));
#pragma unroll
  for (int e = 0; e < 4; e++) {
    const float x = ex2((l[e][0] - dn[e]) * L2E), y = ex2((l[e][1] - dn[e]) * L2E);
    const uint32_t pr = pack2(x, y), mk = (g0 ? 0xFFFFu : 0u) | (g1 ? 0xFFFF0000u : 0u);
    pp[e][0] = pr & mk; pp[e][1] = pr & ~mk;
    dn[e] = x + y;
  }
  float o[8][4];
#pragma unroll
  for (int t = 0; t < 8; t++) {
    o[t][0] = o[t][1] = o[t][2] = o[t][3] = 0.f;
    mma16(o[t], pp[(t >> 2) * 2][0], 0u, pp[(t >> 2) * 2][1], pp[(t >> 2) * 2 + 1][0], hl[8 + t], kv[16 + 8 * H + t][0]);
  }
#pragma unroll
  for (int x = 1; x < 3; x++)
#pragma unroll
    for (int e = 0; e < 4; e++) dn[e] += __shfl_xor_sync(~0u, dn[e], x);
#pragma unroll
  for (int t = 0; t < 8; t++) mma8(o[t], 0u, pp[(t >> 2) * 2 + 1][1], kv[16 + 8 * H + t][1]);
#pragma unroll
  for (int e = 0; e < 4; e++) dn[e] = rcp(dn[e]);
  const uint32_t oa = k.stg + H * 8192 + (k.w * 16 + (k.lane & 15)) * 128;
#pragma unroll
  for (int u = 0; u < 4; u++) {
    const float r0 = dn[u & 2], r1 = dn[(u & 2) + 1];
    stsm4(oa + (((2 * u + (k.lane >> 4)) ^ (k.lane & 7)) << 4), pack2(o[2 * u][0] * r0, o[2 * u][1] * r0), pack2(o[2 * u][2] * r1, o[2 * u][3] * r1),
          pack2(o[2 * u + 1][0] * r0, o[2 * u + 1][1] * r0), pack2(o[2 * u + 1][2] * r1, o[2 * u + 1][3] * r1));
  }
  handoff(c, k, H == 0 ? B_SFA : B_SFULL);
}

template <int CH> __device__ __forceinline__ void epi_res(const float (&acc)[64], uint32_t (&res)[32], float sc0, float sc1, Con& k) {
  const uint32_t oa = k.stg + CH * 8192 + (k.w * 16 + (k.lane & 15)) * 128;
#pragma unroll
  for (int u = 0; u < 4; u++) {
#pragma unroll
    for (int e = 0; e < 4; e++) {
      const int x = 16 * CH + 4 * u + e;
      const float sc = (e & 1) ? sc1 : sc0;
      res[x] = pack2(fmaf(sc, acc[2 * x], bf_lo(res[x])), fmaf(sc, acc[2 * x + 1], bf_hi(res[x])));
    }
    stsm4(oa + (((2 * u + (k.lane >> 4)) ^ (k.lane & 7)) << 4), res[16 * CH + 4 * u], res[16 * CH + 4 * u + 1], res[16 * CH + 4 * u + 2], res[16 * CH + 4 * u + 3]);
  }
}

template <int NCH> __device__ __forceinline__ void epi_ffn1(const float (&acc)[NCH * 32], Pre& a, const Ctx& c, Con& k) {
  const uint32_t csa = c.sb + OFF_CS + (NCH == 4 ? 0 : 1024) + (k.lane & 3) * 16;
  const uint32_t rowo = (k.w * 16 + (k.lane & 15)) * 128;
#pragma unroll
  for (int u = 0; u < NCH * 4; u++) {
    const int ch = u >> 2, t = 8 * u;
    const uint32_t cb = ch < 2 ? k.stg + ch * 8192 : c.sb + OFF_SPARE + k.wg * 8192 + (ch == NCH - 1 ? 16384 : 0);
    const float4 s = a.cs[u & 3];
    const uint32_t v0 = pack2_relu(fmaf(a.s0.x, s.x, acc[t]), fmaf(a.s0.x, s.y, acc[t + 1])), v1 = pack2_relu(fmaf(a.s1.x, s.x, acc[t + 2]), fmaf(a.s1.x, s.y, acc[t + 3]));
    const uint32_t v2 = pack2_relu(fmaf(a.s0.x, s.z, acc[t + 4]), fmaf(a.s0.x, s.w, acc[t + 5])), v3 = pack2_relu(fmaf(a.s1.x, s.z, acc[t + 6]), fmaf(a.s1.x, s.w, acc[t + 7]));
    if (u + 4 < NCH * 4) a.cs[u & 3] = lds128f(csa + (u + 4) * 64);
    stsm4(cb + rowo + ((((2 * u & 7) + (k.lane >> 4)) ^ (k.lane & 7)) << 4), v0, v1, v2, v3);
  }
  handoff(c, k);
}

__device__ __forceinline__ void acc_stat(uint32_t v, float sh, float& s1, float& s2) {
  const float x = bf_lo(v) - sh, y = bf_hi(v) - sh;
  s1 += x + y; s2 = fmaf(y, y, fmaf(x, x, s2));
}
__device__ __forceinline__ float2 row_stat(uint32_t ra, uint32_t xo, float sh) {
  float s1[2] = {0.f, 0.f}, s2[2] = {0.f, 0.f};
  uint4 v[2][2];
#pragma unroll
  for (int e = 0; e < 2; e++) v[0][e] = lds128(ra + ((e * 16) ^ xo));
#pragma unroll 1
  for (int b = 0; b < 4; b++) {
#pragma unroll
    for (int h = 0; h < 2; h++) {
      const int n = (2 * b + h + 1) & 7;
#pragma unroll
      for (int e = 0; e < 2; e++) v[h ^ 1][e] = lds128(ra + (n >> 2) * 8192 + (((n & 3) * 32 + e * 16) ^ xo));
#pragma unroll
      for (int e = 0; e < 2; e++) { acc_stat(v[h][e].x, sh, s1[0], s2[0]); acc_stat(v[h][e].y, sh, s1[1], s2[1]); acc_stat(v[h][e].z, sh, s1[0], s2[0]); acc_stat(v[h][e].w, sh, s1[1], s2[1]); }
    }
  }
  return make_float2(s1[0] + s1[1], s2[0] + s2[1]);
}
template <bool PF> __device__ __forceinline__ void unit_load(const Params& p, int j, int u, uint32_t dst, uint32_t bar) {
  const int ch = u >> 3;
  const CUtensorMap* mp = ch < 6 ? &p.mCq : &p.mC1;
  const int col = ch < 6 ? (ch < 4 ? 1024 + (ch >> 1) * 1024 : 0) + 128 * j + 64 * (ch & 1) : 448 * j + 64 * (ch - 6);
  if (PF) {
    asm volatile("cp.async.bulk.prefetch.tensor.2d.L2.global [%0, {%1, %2}];" ::"l"(mp), "r"(col), "r"((u & 7) * 128) : "memory");
  } else {
    mbar_expect_tx(bar, 16384);
    tma2d(dst, mp, bar, col, (u & 7) * 128);
  }
}
__device__ __forceinline__ void unit_sum(int j, uint32_t tag, int u, uint32_t src, int lane) {
  float s[8];
#pragma unroll
  for (int e = 0; e < 8; e++) s[e] = 0.f;
  uint4 v[2][4];
#pragma unroll
  for (int e = 0; e < 4; e++) v[0][e] = lds128(src + e * 512 + lane * 16);
#pragma unroll 1
  for (int b = 0; b < 4; b++) {
#pragma unroll
    for (int h = 0; h < 2; h++) {
#pragma unroll
      for (int e = 0; e < 4; e++) v[h ^ 1][e] = lds128(src + ((2 * b + h + 1) & 7) * 2048 + e * 512 + lane * 16);
#pragma unroll
      for (int e = 0; e < 4; e++) {
        const uint4 t = v[h][e];
        s[0] += bf_lo(t.x); s[1] += bf_hi(t.x); s[2] += bf_lo(t.y); s[3] += bf_hi(t.y);
        s[4] += bf_lo(t.z); s[5] += bf_hi(t.z); s[6] += bf_lo(t.w); s[7] += bf_hi(t.w);
      }
    }
  }
  const bool hi = lane & 16, md = lane & 8;
#pragma unroll
  for (int e = 0; e < 4; e++) s[e] = (hi ? s[e + 4] : s[e]) + __shfl_xor_sync(~0u, hi ? s[e] : s[e + 4], 16);
#pragma unroll
  for (int e = 0; e < 2; e++) s[e] = (md ? s[e + 2] : s[e]) + __shfl_xor_sync(~0u, md ? s[e] : s[e + 2], 8);
  st_tag2(g_cs + ((u & 7) * 8 + j) * 832 + (u >> 3) * 64 + (lane & 7) * 8 + (lane >> 4) * 4 + (md ? 2 : 0), s[0], s[1], tag);
}
__device__ __forceinline__ void cs_gather(const Ctx& c, int col, int dcol) {
  float4 v[8]; uint32_t bad; int it = 0;
  do {
    bad = 0;
#pragma unroll
    for (int u = 0; u < 8; u++) v[u] = ld_tag4(g_cs + (u * 8 + c.j) * 832 + col);
#pragma unroll
    for (int u = 0; u < 8; u++) bad |= tag_bad(v[u], c.ep1);
    spin_check(it);
  } while (bad);
#pragma unroll
  for (int u = 1; u < 8; u++) { v[0].x += v[u].x; v[0].y += v[u].y; v[0].z += v[u].z; v[0].w += v[u].w; }
  const uint32_t da = c.sb + OFF_CS + (dcol >> 4) * 64 + (dcol & 4) * 8 + (dcol & 8);
  sts64f(da, v[0].x, v[0].y); sts64f(da + 16, v[0].z, v[0].w);
}
__device__ __forceinline__ void halo_relay(const Ctx& c, int T, int a, int lane) {
  uint32_t hl[16];
#pragma unroll
  for (int u = 0; u < 16; u++) hl[u] = 0;
  if (c.i > 0) {
    const uint4* hp = g_halo + ((((c.i - 1) * 8 + c.j) * 2 + a) * 2 + T) * 256 + lane;
    int it = 0; bool ok;
    do {
      ok = true;
#pragma unroll
      for (int u = 0; u < 8; u++) {
        unsigned long long x, y;
        asm volatile("ld.relaxed.gpu.global.v2.b64 {%0, %1}, [%2];" : "=l"(x), "=l"(y) : "l"(hp + u * 32) : "memory");
        hl[2 * u] = (uint32_t)x; hl[2 * u + 1] = (uint32_t)y;
        ok = ok && (uint32_t)(x >> 32) == c.ep1 && (uint32_t)(y >> 32) == c.ep1;
      }
      spin_check(it);
    } while (!ok);
  }
#pragma unroll
  for (int u = 0; u < 4; u++) sts128(c.sb + OFF_STG + a * 16384 + T * 8192 + lane * 16 + u * 512, hl[4 * u], hl[4 * u + 1], hl[4 * u + 2], hl[4 * u + 3]);
}

__device__ __forceinline__ void aux_warp(const Params& p, const Ctx& c, int a, int lane) {
  const uint32_t spare = c.sb + OFF_SPARE, mystg = c.sb + OFF_STG + a * 16384;
  const uint32_t bA = c.bar + 8 * (B_AUX + a), bSF = c.bar + 8 * (B_SFULL + a), bSE = c.bar + 8 * (B_SEMPTY + a);
  const bool lead = (a == 0 && lane == 0);
  const int row0 = 128 * c.i + 64 * a, u0 = 2 * c.i + a;
  const uint32_t tag = c.ep1 & 3, peer = mapa(c.sb, c.rank ^ 1);
  if (lane == 0) {
    if (AUX_GATE >= 0) mbar_wait(c.bar + 8 * AUX_GATE, 0);
    unit_load<false>(p, c.j, u0, mystg, bA);
  }
  mbar_wait(bA, 0);
  if (lead) PROF(4);
  unit_sum(c.j, tag, u0, mystg, lane);
  if (lead) PROF(6);
  {
    float4 v; int it = 0;
    do { v = ld_tag4(g_xst + row0 + 2 * lane); spin_check(it); } while (tag_bad(v, tag));
    sts128(c.sb + OFF_ST + (64 * a + 2 * lane) * 8, __float_as_uint(v.x), __float_as_uint(v.y), __float_as_uint(v.z), __float_as_uint(v.w));
  }
#pragma unroll 1
  for (int r = 0; r < 4; r++) {
    if (r == 2) {
      mbar_wait(bSF, 1);
      if (lane == 0) {
        tma2d_st(&p.mH, mystg, 128 * c.j, row0); tma2d_st(&p.mH, mystg + 8192, 128 * c.j + 64, row0); bulk_commit();
        if (lead) PROF(18);
        wait_empty(c, 46);
        bulk_s2s(peer + 1 * 49152 + a * 8192, mystg, 8192, peer + OFF_BAR + 8 * (50 & 7));
        wait_empty(c, 47);
        bulk_s2s(peer + 2 * 49152 + a * 8192, mystg + 8192, 8192, peer + OFF_BAR + 8 * (51 & 7));
        bulk_wait_all(); flag_add(F_H + c.i * 2 + a);
        if (lead) PROF(19);
      }
      __syncwarp();
#pragma unroll 1
      for (int hh = 0; hh < 2; hh++) {
        const int rr = lane + 32 * hh;
        const uint32_t ra = mystg + rr * 128;
        const float sh = lds_bf16(ra);
        const float2 st = row_stat(ra, (lane & 7) << 4, sh);
        const float lm = st.x * (1.f / 128);
        st_tag2(g_hst + (row0 + rr) * 8 + c.j, sh + lm, fmaf(-st.x, lm, st.y), tag);
      }
      __syncwarp();
      if (lane == 0) mbar_arrive(bSE);
      if (lead) PROF(12);
      {
        float4 v[8]; uint32_t bad; int it = 0;
        do {
          bad = 0;
#pragma unroll
          for (int u = 0; u < 8; u++) v[u] = ld_tag4(g_hst + (row0 + lane + 32 * (u >> 2)) * 8 + 2 * (u & 3));
#pragma unroll
          for (int u = 0; u < 8; u++) bad |= tag_bad(v[u], tag);
          spin_check(it);
        } while (bad);
#pragma unroll
        for (int hh = 0; hh < 2; hh++) {
          const float4* w = v + 4 * hh;
          const float mean = (((w[0].x + w[0].z) + (w[1].x + w[1].z)) + ((w[2].x + w[2].z) + (w[3].x + w[3].z))) * 0.125f;
          float m2 = 0.f, dd = 0.f;
#pragma unroll
          for (int u = 0; u < 4; u++) { m2 += w[u].y + w[u].w; dd += (w[u].x - mean) * (w[u].x - mean) + (w[u].z - mean) * (w[u].z - mean); }
          sts64f(c.sb + OFF_ST + (64 * a + lane + 32 * hh) * 8, mean, rsqrtf(fmaxf(m2 + 128.f * dd, 0.f) * (1.f / D_) + 1e-5f));
        }
      }
    }
    const int nl = r == 1 ? 16 : r == 3 ? 24 : 32, dcol = 256 * (r & 1) + 4 * (nl * a + lane);
    if (lane < nl) cs_gather(c, dcol + 384 * (r >> 1), dcol);
    __syncwarp();
    if (lane == 0) { mbar_arrive(c.bar + 8 * (B_RDY0 + (r & 1))); if (lead) PROF(7 + r); }
    if (r == 1) {
#pragma unroll 1
      for (int t = 0; t < 2; t++) halo_relay(c, t, a, lane);
      __syncwarp();
      if (lane == 0) {
        mbar_arrive(c.bar + 8 * (B_HALO + a));
        if (lead) PROF(11);
#pragma unroll 1
        for (int t = 0; t < 2; t++) {
          mbar_wait(t ? bSF : c.bar + 8 * (B_SFA + a), 0);
          tma2d_st(&p.mO, mystg + t * 8192, 128 * c.j + 64 * t, row0); bulk_commit();
          if (lead) PROF(13 + 3 * t);
          wait_empty(c, 28 + t);
          bulk_s2s(peer + (2 + t) * 32768 + a * 8192, mystg + t * 8192, 8192, peer + OFF_BAR + 8 * (2 + t));
        }
        asm volatile("cp.async.bulk.wait_group 1;" ::: "memory");
        flag_add(F_O + c.i * 4 + a);
        if (lead) PROF(14);
        bulk_wait_all(); flag_add(F_O + c.i * 4 + 2 + a);
        if (lead) PROF(17);
        wait_empty(c, 35);
        mbar_expect_tx(bSE, 16384);
        tma3d(mystg, &p.mX, bSE, 128 * c.j, a, 64 * c.i); tma3d(mystg + 8192, &p.mX, bSE, 128 * c.j + 64, a, 64 * c.i);
      }
      named_sync(3, 64);
    }
    if (r >= 2) {
      if (lane == 0) {
        const int col = 448 * c.j + 256 * (r - 2);
        mbar_wait(bSF, r & 1);
        tma2d_st(&p.mH1, spare + 16384 + a * 8192, col + (r == 2 ? 192 : 128), row0);
        tma2d_st(&p.mH1, mystg, col, row0); tma2d_st(&p.mH1, mystg + 8192, col + 64, row0);
        if (r == 2) tma2d_st(&p.mH1, spare + a * 8192, col + 128, row0);
        bulk_commit(); bulk_wait_read(); mbar_arrive(bSE);
        bulk_wait_all(); flag_add(F_H1 + c.i * 4 + 2 * (r - 2) + a);
        if (lead) PROF(20 + r);
      }
      __syncwarp();
    }
  }
}

__device__ __forceinline__ void helper_unit(int g, int& j, int& u) {
  const int x = g >> 3;
  j = x < 16 ? x >> 1 : x < 48 ? (x - 16) >> 2 : (x - 48) / 3;
  u = 8 * (x < 16 ? 4 + (x & 1) : x < 48 ? 6 + (x & 3) : 10 + x % 3) + (g & 7);
}
__device__ __forceinline__ void helper_warp(const Params& p, const Ctx& c, int g0, int warp, int lane) {
  const uint32_t buf = c.sb + warp * 16384, bar = c.bar + 8 * (warp < 8 ? warp : warp + B_SEMPTY - 8);
#pragma unroll 1
  for (int t = 0; t < 12; t++) {
    int j, u;
    if (t < 11 && lane == 0) { helper_unit(g0 + 48 * t + 48, j, u); unit_load<true>(p, j, u, 0, 0); }
    helper_unit(g0 + 48 * t, j, u);
    if (lane == 0) unit_load<false>(p, j, u, buf, bar);
    mbar_wait(bar, t & 1);
    unit_sum(j, c.ep1 & 3, u, buf, lane);
  }
}

__device__ __forceinline__ uint32_t load_epoch() {
  uint32_t ctr;
  asm volatile("ld.relaxed.gpu.global.u32 %0, [%1];" : "=r"(ctr) : "l"(&g_ctr) : "memory");
  return (ctr >> 7) + 1;
}

__global__ void __cluster_dims__(2, 1, 1) __launch_bounds__(384, 1) fused_block_kernel(const __grid_constant__ Params p) {
  extern __shared__ __align__(1024) uint8_t smem_raw[];
  Ctx c;
  c.sb = (uint32_t)__cvta_generic_to_shared(smem_raw);
  c.bar = c.sb + OFF_BAR;
  c.rank = blockIdx.x & 1;
  int cl = (blockIdx.x >> 1) + (gridDim.x == 4 ? 64 : 0);
  if (LAYOUT && gridDim.x == 132) {
    uint32_t t; asm("mov.u32 %0, %%smid;" : "=r"(t));
    t >>= 1;
    cl = t < 32 ? (t & 7) * 8 + (t >> 3) : t < 60 ? (1 + (t - 32) % 7) * 8 + 4 + (t - 32) / 7 : t < 62 ? t + 4 : t - 58;
  }
  const bool helper = cl >= 64;
  if (LAYOUT == 0) { c.i = cl & 15; c.j = (cl >> 4) * 2 + c.rank; }
  if (LAYOUT == 1) { c.i = ((cl >> 4) & 3) * 4 + (cl & 3); c.j = ((cl >> 2) & 3) * 2 + c.rank; }
  if (LAYOUT == 2) { c.i = (cl >> 2) & 15; c.j = (cl & 3) * 2 + c.rank; }
  if (LAYOUT == 3) { c.i = cl & 15; c.j = ((cl >> 4) & 3) * 2 + c.rank; }
  const int warp = __shfl_sync(~0u, threadIdx.x >> 5, 0), lane = threadIdx.x & 31;
  if (warp == 8 && lane == 0) {
    PROF(0);
    asm volatile("{\n.reg .pred p;\nsetp.ne.u32 p, %0, %1;\n@p trap;\n}\n" ::"r"(c.sb & 0x3FFFF), "n"(SMEM_BASE));
    map_prefetch(&p.mWkv);
#pragma unroll
    for (int s = 0; s < B_NUM; s++) mbar_init(c.bar + 8 * s, (s < B_EMPTY || s >= B_SEMPTY) ? 1 : (s >= B_RDY0 ? 2 : 4));
    asm volatile("fence.mbarrier_init.release.cluster;" ::: "memory");
    fence_async_smem();
  }
  if (warp == 9 && lane == 0 && !helper) {
    map_prefetch(&p.mX);
#pragma unroll
    for (int s = 0; s < 4; s++) tma3d_prefetch(&p.mX, 64 * s, c.rank, 64 * c.i);
  }
  if (warp == 10 && lane == 0) {
#pragma unroll
    for (int s = 2; s < 13; s++) map_prefetch(&p.mX + s);
  }
  __syncwarp();
  asm volatile("barrier.cluster.arrive.relaxed.aligned;" ::: "memory");
  if (warp == 8 && lane == 0 && !helper) produce_b<0>(p, c, 0, 4);
  __syncwarp();
  asm volatile("barrier.cluster.wait.acquire.aligned;" ::: "memory");
  if (helper) {
    c.ep1 = load_epoch();
    helper_warp(p, c, ((cl & 1) * 2 + c.rank) * 12 + warp, warp, lane);
  } else if (warp >= 8) {
    asm volatile("setmaxnreg.dec.sync.aligned.u32 88;");
    if (warp == 8) {
      if (lane == 0) {
        PROF(1);
        produce_b<0>(p, c, 4, 16); produce_b<1>(p, c, 0, 16); produce_b<2>(p, c, 0, 16); produce_b<3>(p, c, 0, 16); produce_b<4>(p, c, 0, 16); produce_b<5>(p, c, 0, 56);
        asm volatile("red.relaxed.gpu.global.add.u32 [%0], 1;" ::"l"(&g_ctr) : "memory");
      }
    } else if (warp == 9) {
      if (lane == 0) { produce_a<0>(p, c); c.ep1 = load_epoch(); produce_a<1>(p, c); produce_a<2>(p, c); produce_a<3>(p, c); produce_a<4>(p, c); produce_a<5>(p, c); }
    } else {
      c.ep1 = load_epoch();
      aux_warp(p, c, warp - 10, lane);
    }
  } else {
    asm volatile("setmaxnreg.inc.sync.aligned.u32 208;");
    c.ep1 = load_epoch();
    Con k;
    k.wg = warp >> 2; k.w = warp & 3; k.lane = lane; k.spin = 0;
    k.do_rel = (threadIdx.x & 127) < 2;
    k.rel = mapa(c.bar + 8 * B_EMPTY, threadIdx.x & 1);
    k.stg = c.sb + OFF_STG + k.wg * 16384;
    k.da = ((SMEM_BASE >> 4) | (1u << 16)) + k.wg * 512;
    uint32_t kv[32][2];
    {
      float acc[128]; Pre pr;
      const int rb = 16 * c.j + 2 * warp + (lane >> 4);
      const uint4* xr = reinterpret_cast<const uint4*>(p.x + (size_t)(128 * c.i + rb) * D_) + (lane & 15);
      uint4 xv[8];
      if (XLD_EARLY) {
#pragma unroll
        for (int e = 0; e < 8; e++) xv[e] = ldcg128(xr + 16 * e);
      }
      ISSUE0(0, acc);
      if (!XLD_EARLY) {
#pragma unroll
        for (int e = 0; e < 8; e++) xv[e] = ldcg128(xr + 16 * e);
      }
      steps<0>(acc, c, k, 1, XST);
      ISSUE(0, acc, XST);
      const float sh = __shfl_sync(~0u, bf_lo(xv[0].x), lane & 16);
      float s1[2] = {0.f, 0.f}, s2[2] = {0.f, 0.f};
#pragma unroll
      for (int e = 0; e < 8; e++) {
        acc_stat(xv[e].x, sh, s1[0], s2[0]); acc_stat(xv[e].y, sh, s1[1], s2[1]); acc_stat(xv[e].z, sh, s1[0], s2[0]); acc_stat(xv[e].w, sh, s1[1], s2[1]);
        if (e == 4) { asm volatile("" : "+f"(s1[0]), "+f"(s1[1]), "+f"(s2[0]), "+f"(s2[1])); retire<0>(k, XST); ISSUE(0, acc, XST + 1); }
      }
      float t1 = s1[0] + s1[1], t2 = s2[0] + s2[1];
#pragma unroll
      for (int o = 1; o < 16; o <<= 1) { t1 += __shfl_xor_sync(~0u, t1, o); t2 += __shfl_xor_sync(~0u, t2, o); }
      t1 *= 1.f / D_;
      if ((lane & 15) == 0) st_tag2(g_xst + 128 * c.i + 64 * (rb & 1) + (rb >> 1), sh + t1, rsqrtf(fmaxf(fmaf(-t1, t1, t2 * (1.f / D_)), 0.f) + 1e-5f), c.ep1 & 3);
      if (threadIdx.x == 0) PROF(5);
      retire<0>(k, XST + 1);
      steps<0>(acc, c, k, XST + 2, 15);
      ISSUE(0, acc, 15); pre_load<0>(pr, c, k); retire<0>(k, 15);
      finish<0>(k);
      qkv_pack<0, 0, 16>(kv, acc, pr, c, k);
      if (k.do_rel) PROF(32 + 32 * k.wg + 2);
    }
    {
      float acc[64]; Pre pr; uint32_t q[16][2];
      ISSUE0(1, acc);
#pragma unroll
      for (int t = 16; t < 32; t++) kv[t][0] = movm(kv[t][0]);
      ISSUE(1, acc, 1); halo_publish(kv, c, k); retire<1>(k, 1);
      steps<1>(acc, c, k, 2, 15);
      ISSUE(1, acc, 15); pre_load<1>(pr, c, k); retire<1>(k, 15);
      finish<1>(k);
      const float sc0 = pr.s0.y * 0.17677669529663687f, sc1 = pr.s1.y * 0.17677669529663687f;
      qkv_pack<1, 0, 4>(q, acc, pr, c, k);
      attend<0>(q, kv, sc0, sc1, c, k);
      if (k.do_rel) PROF(32 + 32 * k.wg + 23);
      qkv_pack<1, 4, 8>(q, acc, pr, c, k);
      attend<1>(q, kv, sc0, sc1, c, k);
      if (k.do_rel) PROF(32 + 32 * k.wg + 5);
      mbar_wait_u(c.bar + 8 * (B_SFULL + k.wg), 0, k.spin);
    }
    uint32_t res[32];
    {
      float acc[64];
      ISSUE0(2, acc);
      steps<2>(acc, c, k, 1, 15);
      ISSUE(2, acc, 15);
      mbar_wait_u(c.bar + 8 * (B_SEMPTY + k.wg), 0, k.spin);
#pragma unroll
      for (int u = 0; u < 8; u++)
        ldsm4(k.stg + (u >> 2) * 8192 + (k.w * 16 + (lane & 15)) * 128 + ((((2 * u & 7) + (lane >> 4)) ^ (lane & 7)) << 4), res[4 * u], res[4 * u + 1], res[4 * u + 2], res[4 * u + 3]);
      retire<2>(k, 15);
      finish<2>(k);
      epi_res<0>(acc, res, 1.f, 1.f, k); epi_res<1>(acc, res, 1.f, 1.f, k);
      handoff(c, k);
      if (k.do_rel) PROF(32 + 32 * k.wg + 8);
      mbar_wait_u(c.bar + 8 * (B_SFULL + k.wg), 1, k.spin);
    }
    {
      float acc[128]; Pre pr;
      ISSUE0(3, acc);
      steps<3>(acc, c, k, 1, 15);
      ISSUE(3, acc, 15); pre_load<3>(pr, c, k); retire<3>(k, 15);
      finish<3>(k);
      epi_ffn1<4>(acc, pr, c, k);
      if (k.do_rel) PROF(32 + 32 * k.wg + 11);
    }
    {
      float acc[96]; Pre pr;
      ISSUE0(4, acc);
      steps<4>(acc, c, k, 1, 15);
      ISSUE(4, acc, 15); pre_load<4>(pr, c, k); retire<4>(k, 15);
      finish<4>(k);
      epi_ffn1<3>(acc, pr, c, k);
      if (k.do_rel) PROF(32 + 32 * k.wg + 14);
    }
    {
      float acc[64];
      ISSUE0(5, acc);
      steps<5>(acc, c, k, 1, 56);
      const uint32_t sta = c.sb + OFF_ST + (k.wg * 64 + k.w * 16 + (lane >> 2)) * 8;
      const float sc0 = lds64f(sta).y, sc1 = lds64f(sta + 64).y;
      mbar_wait_u(c.bar + 8 * (B_SEMPTY + k.wg), 1, k.spin);
      spin_check(k.spin);
      finish<5>(k);
      epi_res<0>(acc, res, sc0, sc1, k);
      fence_async_smem(); __syncwarp();
      if (lane == 0) tma3d_st(&p.mOut, k.stg + k.w * 2048, 128 * c.j, k.wg, 64 * c.i + 16 * k.w);
      epi_res<1>(acc, res, sc0, sc1, k);
      fence_async_smem(); __syncwarp();
      if (k.do_rel) PROF(32 + 32 * k.wg + 17);
      if (lane == 0) { tma3d_st(&p.mOut, k.stg + 8192 + k.w * 2048, 128 * c.j + 64, k.wg, 64 * c.i + 16 * k.w); bulk_commit(); bulk_wait_read(); }
      if (k.do_rel) PROF(32 + 32 * k.wg + 18);
    }
  }
}

typedef CUresult (*EncFn)(CUtensorMap*, CUtensorMapDataType, cuuint32_t, void*, const cuuint64_t*, const cuuint64_t*, const cuuint32_t*,
                          const cuuint32_t*, CUtensorMapInterleave, CUtensorMapSwizzle, CUtensorMapL2promotion, CUtensorMapFloatOOBfill);

void enc(EncFn f, CUtensorMap* m, const void* ptr, int rank, cuuint64_t d0, cuuint64_t d1, cuuint64_t d2, cuuint64_t s1, cuuint64_t s2,
         cuuint32_t b0, cuuint32_t b1, cuuint32_t b2, CUtensorMapSwizzle sw = CU_TENSOR_MAP_SWIZZLE_128B) {
  const cuuint64_t dims[3] = {d0, d1, d2}, str[2] = {s1, s2};
  const cuuint32_t box[3] = {b0, b1, b2}, es[3] = {1, 1, 1};
  f(m, CU_TENSOR_MAP_DATA_TYPE_BFLOAT16, rank, const_cast<void*>(ptr), dims, str, box, es, CU_TENSOR_MAP_INTERLEAVE_NONE,
    sw, CU_TENSOR_MAP_L2_PROMOTION_L2_256B, CU_TENSOR_MAP_FLOAT_OOB_FILL_NONE);
}

}

extern "C" void kernel_launch(void* const* d_in, const int* in_sizes, int n_in, void* d_out, int out_size) {
  (void)in_sizes; (void)n_in; (void)out_size;
  const void *x = d_in[0], *wqkv = d_in[1], *wo = d_in[2], *w1 = d_in[4], *w2 = d_in[5];
  EncFn f = nullptr;
  cudaDriverEntryPointQueryResult qr;
  cudaGetDriverEntryPoint("cuTensorMapEncodeTiled", (void**)&f, cudaEnableDefault, &qr);
  void *po, *ph, *ph1;
  cudaGetSymbolAddress(&po, g_o); cudaGetSymbolAddress(&ph, g_h); cudaGetSymbolAddress(&ph1, g_h1);
  Params p;
  enc(f, &p.mX, x, 3, D_, 2, S_ / 2, D_ * 2, D_ * 4, 64, 1, 64);
  enc(f, &p.mOut, d_out, 3, D_, 2, S_ / 2, D_ * 2, D_ * 4, 64, 1, 16);
  enc(f, &p.mCq, wqkv, 2, 3 * D_, D_, 1, 3 * D_ * 2, 0, 64, 128, 1, CU_TENSOR_MAP_SWIZZLE_NONE);
  enc(f, &p.mC1, w1, 2, F_, D_, 1, F_ * 2, 0, 64, 128, 1, CU_TENSOR_MAP_SWIZZLE_NONE);
  {
    const cuuint64_t dims[4] = {64, D_, D_ / 64, 3}, str[3] = {3 * D_ * 2, 128, D_ * 2};
    const cuuint32_t box[4] = {64, 64, 2, 2}, es[4] = {1, 1, 1, 1};
    f(&p.mWkv, CU_TENSOR_MAP_DATA_TYPE_BFLOAT16, 4, const_cast<void*>(wqkv), dims, str, box, es, CU_TENSOR_MAP_INTERLEAVE_NONE,
      CU_TENSOR_MAP_SWIZZLE_128B, CU_TENSOR_MAP_L2_PROMOTION_L2_256B, CU_TENSOR_MAP_FLOAT_OOB_FILL_NONE);
  }
  enc(f, &p.mWq, wqkv, 3, 64, D_, D_ / 64, 3 * D_ * 2, 128, 64, 64, 2);
  enc(f, &p.mWo, wo, 3, 64, D_, D_ / 64, D_ * 2, 128, 64, 64, 2);
  enc(f, &p.mW1a, w1, 3, 64, D_, F_ / 64, F_ * 2, 128, 64, 64, 4);
  enc(f, &p.mW1b, w1, 3, 64, D_, F_ / 64, F_ * 2, 128, 64, 64, 3);
  enc(f, &p.mW2, w2, 3, 64, F_, D_ / 64, D_ * 2, 128, 64, 64, 2);
  enc(f, &p.mO, po, 2, D_, S_, 1, D_ * 2, 0, 64, 64, 1);
  enc(f, &p.mH, ph, 2, D_, S_, 1, D_ * 2, 0, 64, 64, 1);
  enc(f, &p.mH1, ph1, 2, F_, S_, 1, F_ * 2, 0, 64, 64, 1);
  p.x = (const bf16*)x;
  cudaFuncSetAttribute(fused_block_kernel, cudaFuncAttributeMaxDynamicSharedMemorySize, SMEM_BYTES);
  cudaLaunchConfig_t cfg = {};
  cudaLaunchAttribute at;
  at.id = cudaLaunchAttributeClusterDimension; at.val.clusterDim.x = 2; at.val.clusterDim.y = 1; at.val.clusterDim.z = 1;
  cfg.gridDim = dim3(132); cfg.blockDim = dim3(384); cfg.dynamicSmemBytes = SMEM_BYTES; cfg.attrs = &at; cfg.numAttrs = 1;
  int ncl = 0;
  cudaOccupancyMaxActiveClusters(&ncl, fused_block_kernel, &cfg);
  if (ncl >= 66) {
    fused_block_kernel<<<132, 384, SMEM_BYTES>>>(p);
  } else {
    fused_block_kernel<<<4, 384, SMEM_BYTES>>>(p);
    fused_block_kernel<<<128, 384, SMEM_BYTES>>>(p);
  }
}
```

```cpp
#include <cuda_runtime.h>
#include <cuda_bf16.h>
#include <cuda.h>
#include <stdint.h>

namespace {

template <int FIRST> __device__ __forceinline__ void wgmma4_n128(float (&d)[64], uint32_t a, uint32_t b) {
#define WGD "{%0, %1, %2, %3, %4, %5, %6, %7, %8, %9, %10, %11, %12, %13, %14, %15, %16, %17, %18, %19, %20, %21, %22, %23, %24, %25, %26, %27, %28, %29, %30, %31, %32, %33, %34, %35, %36, %37, %38, %39, %40, %41, %42, %43, %44, %45, %46, %47, %48, %49, %50, %51, %52, %53, %54, %55, %56, %57, %58, %59, %60, %61, %62, %63}"
  asm volatile("{\n.reg .pred p, q;\n.reg .b64 da, db;\n.reg .b32 x, y;\nsetp.eq.b32 p, %66, 0;\nsetp.eq.b32 q, 0, 0;\n"
    "add.s32 x, %64, 0;\nadd.s32 y, %65, 0;\nmov.b64 da, {x, %67};\nmov.b64 db, {y, %67};\n"
    "wgmma.mma_async.sync.aligned.m64n128k16.f32.bf16.bf16 " WGD ", da, db, p, 1, 1, 0, 1;\n"
    "add.s32 x, %64, 2;\nadd.s32 y, %65, 128;\nmov.b64 da, {x, %67};\nmov.b64 db, {y, %67};\n"
    "wgmma.mma_async.sync.aligned.m64n128k16.f32.bf16.bf16 " WGD ", da, db, q, 1, 1, 0, 1;\n"
    "add.s32 x, %64, 4;\nadd.s32 y, %65, 256;\nmov.b64 da, {x, %67};\nmov.b64 db, {y, %67};\n"
    "wgmma.mma_async.sync.aligned.m64n128k16.f32.bf16.bf16 " WGD ", da, db, q, 1, 1, 0, 1;\n"
    "add.s32 x, %64, 6;\nadd.s32 y, %65, 384;\nmov.b64 da, {x, %67};\nmov.b64 db, {y, %67};\n"
    "wgmma.mma_async.sync.aligned.m64n128k16.f32.bf16.bf16 " WGD ", da, db, q, 1, 1, 0, 1;\n"
    "}\n"
    : "+f"(d[0]), "+f"(d[1]), "+f"(d[2]), "+f"(d[3]), "+f"(d[4]), "+f"(d[5]), "+f"(d[6]), "+f"(d[7]),
      "+f"(d[8]), "+f"(d[9]), "+f"(d[10]), "+f"(d[11]), "+f"(d[12]), "+f"(d[13]), "+f"(d[14]), "+f"(d[15]),
      "+f"(d[16]), "+f"(d[17]), "+f"(d[18]), "+f"(d[19]), "+f"(d[20]), "+f"(d[21]), "+f"(d[22]), "+f"(d[23]),
      "+f"(d[24]), "+f"(d[25]), "+f"(d[26]), "+f"(d[27]), "+f"(d[28]), "+f"(d[29]), "+f"(d[30]), "+f"(d[31]),
      "+f"(d[32]), "+f"(d[33]), "+f"(d[34]), "+f"(d[35]), "+f"(d[36]), "+f"(d[37]), "+f"(d[38]), "+f"(d[39]),
      "+f"(d[40]), "+f"(d[41]), "+f"(d[42]), "+f"(d[43]), "+f"(d[44]), "+f"(d[45]), "+f"(d[46]), "+f"(d[47]),
      "+f"(d[48]), "+f"(d[49]), "+f"(d[50]), "+f"(d[51]), "+f"(d[52]), "+f"(d[53]), "+f"(d[54]), "+f"(d[55]),
      "+f"(d[56]), "+f"(d[57]), "+f"(d[58]), "+f"(d[59]), "+f"(d[60]), "+f"(d[61]), "+f"(d[62]), "+f"(d[63])
    : "r"(a), "r"(b), "n"(FIRST), "r"(0x40000040));
#undef WGD
}

template <int FIRST> __device__ __forceinline__ void wgmma4_n192(float (&d)[96], uint32_t a, uint32_t b) {
#define WGD "{%0, %1, %2, %3, %4, %5, %6, %7, %8, %9, %10, %11, %12, %13, %14, %15, %16, %17, %18, %19, %20, %21, %22, %23, %24, %25, %26, %27, %28, %29, %30, %31, %32, %33, %34, %35, %36, %37, %38, %39, %40, %41, %42, %43, %44, %45, %46, %47, %48, %49, %50, %51, %52, %53, %54, %55, %56, %57, %58, %59, %60, %61, %62, %63, %64, %65, %66, %67, %68, %69, %70, %71, %72, %73, %74, %75, %76, %77, %78, %79, %80, %81, %82, %83, %84, %85, %86, %87, %88, %89, %90, %91, %92, %93, %94, %95}"
  asm volatile("{\n.reg .pred p, q;\n.reg .b64 da, db;\n.reg .b32 x, y;\nsetp.eq.b32 p, %98, 0;\nsetp.eq.b32 q, 0, 0;\n"
    "add.s32 x, %96, 0;\nadd.s32 y, %97, 0;\nmov.b64 da, {x, %99};\nmov.b64 db, {y, %99};\n"
    "wgmma.mma_async.sync.aligned.m64n192k16.f32.bf16.bf16 " WGD ", da, db, p, 1, 1, 0, 1;\n"
    "add.s32 x, %96, 2;\nadd.s32 y, %97, 128;\nmov.b64 da, {x, %99};\nmov.b64 db, {y, %99};\n"
    "wgmma.mma_async.sync.aligned.m64n192k16.f32.bf16.bf16 " WGD ", da, db, q, 1, 1, 0, 1;\n"
    "add.s32 x, %96, 4;\nadd.s32 y, %97, 256;\nmov.b64 da, {x, %99};\nmov.b64 db, {y, %99};\n"
    "wgmma.mma_async.sync.aligned.m64n192k16.f32.bf16.bf16 " WGD ", da, db, q, 1, 1, 0, 1;\n"
    "add.s32 x, %96, 6;\nadd.s32 y, %97, 384;\nmov.b64 da, {x, %99};\nmov.b64 db, {y, %99};\n"
    "wgmma.mma_async.sync.aligned.m64n192k16.f32.bf16.bf16 " WGD ", da, db, q, 1, 1, 0, 1;\n"
    "}\n"
    : "+f"(d[0]), "+f"(d[1]), "+f"(d[2]), "+f"(d[3]), "+f"(d[4]), "+f"(d[5]), "+f"(d[6]), "+f"(d[7]),
      "+f"(d[8]), "+f"(d[9]), "+f"(d[10]), "+f"(d[11]), "+f"(d[12]), "+f"(d[13]), "+f"(d[14]), "+f"(d[15]),
      "+f"(d[16]), "+f"(d[17]), "+f"(d[18]), "+f"(d[19]), "+f"(d[20]), "+f"(d[21]), "+f"(d[22]), "+f"(d[23]),
      "+f"(d[24]), "+f"(d[25]), "+f"(d[26]), "+f"(d[27]), "+f"(d[28]), "+f"(d[29]), "+f"(d[30]), "+f"(d[31]),
      "+f"(d[32]), "+f"(d[33]), "+f"(d[34]), "+f"(d[35]), "+f"(d[36]), "+f"(d[37]), "+f"(d[38]), "+f"(d[39]),
      "+f"(d[40]), "+f"(d[41]), "+f"(d[42]), "+f"(d[43]), "+f"(d[44]), "+f"(d[45]), "+f"(d[46]), "+f"(d[47]),
      "+f"(d[48]), "+f"(d[49]), "+f"(d[50]), "+f"(d[51]), "+f"(d[52]), "+f"(d[53]), "+f"(d[54]), "+f"(d[55]),
      "+f"(d[56]), "+f"(d[57]), "+f"(d[58]), "+f"(d[59]), "+f"(d[60]), "+f"(d[61]), "+f"(d[62]), "+f"(d[63]),
      "+f"(d[64]), "+f"(d[65]), "+f"(d[66]), "+f"(d[67]), "+f"(d[68]), "+f"(d[69]), "+f"(d[70]), "+f"(d[71]),
      "+f"(d[72]), "+f"(d[73]), "+f"(d[74]), "+f"(d[75]), "+f"(d[76]), "+f"(d[77]), "+f"(d[78]), "+f"(d[79]),
      "+f"(d[80]), "+f"(d[81]), "+f"(d[82]), "+f"(d[83]), "+f"(d[84]), "+f"(d[85]), "+f"(d[86]), "+f"(d[87]),
      "+f"(d[88]), "+f"(d[89]), "+f"(d[90]), "+f"(d[91]), "+f"(d[92]), "+f"(d[93]), "+f"(d[94]), "+f"(d[95])
    : "r"(a), "r"(b), "n"(FIRST), "r"(0x40000040));
#undef WGD
}

template <int FIRST> __device__ __forceinline__ void wgmma4_n256(float (&d)[128], uint32_t a, uint32_t b) {
#define WGD "{%0, %1, %2, %3, %4, %5, %6, %7, %8, %9, %10, %11, %12, %13, %14, %15, %16, %17, %18, %19, %20, %21, %22, %23, %24, %25, %26, %27, %28, %29, %30, %31, %32, %33, %34, %35, %36, %37, %38, %39, %40, %41, %42, %43, %44, %45, %46, %47, %48, %49, %50, %51, %52, %53, %54, %55, %56, %57, %58, %59, %60, %61, %62, %63, %64, %65, %66, %67, %68, %69, %70, %71, %72, %73, %74, %75, %76, %77, %78, %79, %80, %81, %82, %83, %84, %85, %86, %87, %88, %89, %90, %91, %92, %93, %94, %95, %96, %97, %98, %99, %100, %101, %102, %103, %104, %105, %106, %107, %108, %109, %110, %111, %112, %113, %114, %115, %116, %117, %118, %119, %120, %121, %122, %123, %124, %125, %126, %127}"
  asm volatile("{\n.reg .pred p, q;\n.reg .b64 da, db;\n.reg .b32 x, y;\nsetp.eq.b32 p, %130, 0;\nsetp.eq.b32 q, 0, 0;\n"
    "add.s32 x, %128, 0;\nadd.s32 y, %129, 0;\nmov.b64 da, {x, %131};\nmov.b64 db, {y, %131};\n"
    "wgmma.mma_async.sync.aligned.m64n256k16.f32.bf16.bf16 " WGD ", da, db, p, 1, 1, 0, 1;\n"
    "add.s32 x, %128, 2;\nadd.s32 y, %129, 128;\nmov.b64 da, {x, %131};\nmov.b64 db, {y, %131};\n"
    "wgmma.mma_async.sync.aligned.m64n256k16.f32.bf16.bf16 " WGD ", da, db, q, 1, 1, 0, 1;\n"
    "add.s32 x, %128, 4;\nadd.s32 y, %129, 256;\nmov.b64 da, {x, %131};\nmov.b64 db, {y, %131};\n"
    "wgmma.mma_async.sync.aligned.m64n256k16.f32.bf16.bf16 " WGD ", da, db, q, 1, 1, 0, 1;\n"
    "add.s32 x, %128, 6;\nadd.s32 y, %129, 384;\nmov.b64 da, {x, %131};\nmov.b64 db, {y, %131};\n"
    "wgmma.mma_async.sync.aligned.m64n256k16.f32.bf16.bf16 " WGD ", da, db, q, 1, 1, 0, 1;\n"
    "}\n"
    : "+f"(d[0]), "+f"(d[1]), "+f"(d[2]), "+f"(d[3]), "+f"(d[4]), "+f"(d[5]), "+f"(d[6]), "+f"(d[7]),
      "+f"(d[8]), "+f"(d[9]), "+f"(d[10]), "+f"(d[11]), "+f"(d[12]), "+f"(d[13]), "+f"(d[14]), "+f"(d[15]),
      "+f"(d[16]), "+f"(d[17]), "+f"(d[18]), "+f"(d[19]), "+f"(d[20]), "+f"(d[21]), "+f"(d[22]), "+f"(d[23]),
      "+f"(d[24]), "+f"(d[25]), "+f"(d[26]), "+f"(d[27]), "+f"(d[28]), "+f"(d[29]), "+f"(d[30]), "+f"(d[31]),
      "+f"(d[32]), "+f"(d[33]), "+f"(d[34]), "+f"(d[35]), "+f"(d[36]), "+f"(d[37]), "+f"(d[38]), "+f"(d[39]),
      "+f"(d[40]), "+f"(d[41]), "+f"(d[42]), "+f"(d[43]), "+f"(d[44]), "+f"(d[45]), "+f"(d[46]), "+f"(d[47]),
      "+f"(d[48]), "+f"(d[49]), "+f"(d[50]), "+f"(d[51]), "+f"(d[52]), "+f"(d[53]), "+f"(d[54]), "+f"(d[55]),
      "+f"(d[56]), "+f"(d[57]), "+f"(d[58]), "+f"(d[59]), "+f"(d[60]), "+f"(d[61]), "+f"(d[62]), "+f"(d[63]),
      "+f"(d[64]), "+f"(d[65]), "+f"(d[66]), "+f"(d[67]), "+f"(d[68]), "+f"(d[69]), "+f"(d[70]), "+f"(d[71]),
      "+f"(d[72]), "+f"(d[73]), "+f"(d[74]), "+f"(d[75]), "+f"(d[76]), "+f"(d[77]), "+f"(d[78]), "+f"(d[79]),
      "+f"(d[80]), "+f"(d[81]), "+f"(d[82]), "+f"(d[83]), "+f"(d[84]), "+f"(d[85]), "+f"(d[86]), "+f"(d[87]),
      "+f"(d[88]), "+f"(d[89]), "+f"(d[90]), "+f"(d[91]), "+f"(d[92]), "+f"(d[93]), "+f"(d[94]), "+f"(d[95]),
      "+f"(d[96]), "+f"(d[97]), "+f"(d[98]), "+f"(d[99]), "+f"(d[100]), "+f"(d[101]), "+f"(d[102]), "+f"(d[103]),
      "+f"(d[104]), "+f"(d[105]), "+f"(d[106]), "+f"(d[107]), "+f"(d[108]), "+f"(d[109]), "+f"(d[110]), "+f"(d[111]),
      "+f"(d[112]), "+f"(d[113]), "+f"(d[114]), "+f"(d[115]), "+f"(d[116]), "+f"(d[117]), "+f"(d[118]), "+f"(d[119]),
      "+f"(d[120]), "+f"(d[121]), "+f"(d[122]), "+f"(d[123]), "+f"(d[124]), "+f"(d[125]), "+f"(d[126]), "+f"(d[127])
    : "r"(a), "r"(b), "n"(FIRST), "r"(0x40000040));
#undef WGD
}

#define NSL 100
#define HDLY 0
#define PFN 1
#define NB0 1
#define NA0 1
#define XL 1
#define GS 56
#define GH 23
#define G0 9
#define EARLY2B 0
#define EARLY2 0
#define HFEN 0
#define MPF 55
#define PACEH 1
#define PACE4 6
#define PACE3 2
#define PACE 2
#define ROT3 8
#define HPF2 0
#define M5 15
#define SH4 1
#define SH3 1
#define SH0 1
#define PK0 3
#define ACQ 1
#define HORD 1
#define AUX_GATE 3
#define XLD_EARLY 0
#define XST 7
#define RELFLAG 1
#define LAYOUT 3
typedef __nv_bfloat16 bf16;
constexpr int S_ = 2048, D_ = 1024, F_ = 3584;
constexpr int OFF_SPARE = 160 * 1024, OFF_STG = 192 * 1024, OFF_CS = 224 * 1024, OFF_ST = OFF_CS + 1792, OFF_BAR = OFF_ST + 1024;
constexpr int SMEM_BYTES = 232448;
constexpr uint32_t SMEM_BASE = 1024;
enum { B_FULL = 0, B_EMPTY = 8, B_SFULL = 16, B_SFA = 18, B_HALO = 20, B_RDY0 = 22, B_RDY1 = 23, B_SEMPTY = 24, B_AUX = 26, B_NUM = 28, B_PEEK = 28 };
enum { F_O = 0, F_H = 64, F_H1 = 128, F_NUM = 192 };

struct Params {
  CUtensorMap mX, mWkv, mWq, mCq, mC1, mWo, mW1a, mW1b, mW2, mO, mH, mH1, mOut;
  const bf16 *x, *w;
};

__device__ __align__(1024) bf16 g_o[S_ * D_];
__device__ __align__(1024) bf16 g_h[S_ * D_];
__device__ __align__(1024) bf16 g_h1[S_ * F_];
__device__ __align__(128) float2 g_xst[2 * S_];
__device__ __align__(128) float2 g_hst[S_ * 8];
__device__ __align__(128) float g_cs[8 * 8 * 832];
__device__ __align__(128) uint4 g_halo[16 * 8 * 2 * 2 * 256];
__device__ __align__(128) uint32_t g_flag[F_NUM * 8];
__device__ uint32_t g_ctr;
#define PROF(idx) do {} while (0)

constexpr int SPIN_LIMIT = 1 << 22;

__device__ __forceinline__ void mbar_init(uint32_t bar, uint32_t cnt) { asm volatile("mbarrier.init.shared::cta.b64 [%0], %1;" ::"r"(bar), "r"(cnt)); }
__device__ __forceinline__ void mbar_expect_tx(uint32_t bar, uint32_t bytes) { asm volatile("mbarrier.arrive.expect_tx.shared::cta.b64 _, [%0], %1;" ::"r"(bar), "r"(bytes) : "memory"); }
__device__ __forceinline__ void mbar_arrive(uint32_t bar) { asm volatile("mbarrier.arrive.shared::cta.b64 _, [%0];" ::"r"(bar) : "memory"); }
__device__ __forceinline__ void mbar_arrive_cl(uint32_t bar_cluster_addr) { asm volatile("mbarrier.arrive.shared::cluster.b64 _, [%0];" ::"r"(bar_cluster_addr) : "memory"); }
__device__ __forceinline__ uint32_t mapa(uint32_t a, uint32_t cta) { uint32_t r; asm("mapa.shared::cluster.u32 %0, %1, %2;" : "=r"(r) : "r"(a), "r"(cta)); return r; }
__device__ __forceinline__ void spin_check(int& it) { asm volatile("{\n.reg .pred p;\nsetp.gt.s32 p, %0, %1;\n@p trap;\n}\n" ::"r"(++it), "n"(SPIN_LIMIT)); }
__device__ __forceinline__ void mbar_wait(uint32_t bar, uint32_t parity) {
  asm volatile("{\n.reg .pred p;\n.reg .s32 n;\nmov.s32 n, 0;\n"
               "W: mbarrier.try_wait.parity.shared::cta.b64 p, [%0], %1;\n@p bra D;\n"
               "add.s32 n, n, 1;\nsetp.lt.s32 p, n, %2;\n@p bra W;\ntrap;\nD:\n}\n" ::"r"(bar), "r"(parity), "n"(SPIN_LIMIT) : "memory");
}
__device__ __forceinline__ void mbar_wait_u(uint32_t bar, uint32_t parity, int& n) {
  asm volatile("{\n.reg .pred p;\n"
               "W: mbarrier.try_wait.parity.shared::cta.b64 p, [%1], %2;\n@!p add.s32 %0, %0, 1;\n"
               "setp.lt.and.s32 p, %0, %3, !p;\n@p bra.uni W;\n}\n" : "+r"(n) : "r"(bar), "r"(parity), "n"(SPIN_LIMIT) : "memory");
}
__device__ __forceinline__ void flag_add(int f) {
  if (RELFLAG) asm volatile("red.relaxed.gpu.global.add.u32 [%0], 1;" ::"l"(g_flag + f * 8) : "memory");
  else asm volatile("red.release.gpu.global.add.u32 [%0], 1;" ::"l"(g_flag + f * 8) : "memory");
}
__device__ __forceinline__ void flag_wait(int f, uint32_t target) {
  uint32_t v; int it = 0;
  do {
    if (ACQ) asm volatile("ld.acquire.gpu.global.u32 %0, [%1];" : "=r"(v) : "l"(g_flag + f * 8) : "memory");
    else asm volatile("ld.relaxed.gpu.global.u32 %0, [%1];" : "=r"(v) : "l"(g_flag + f * 8) : "memory");
    spin_check(it);
  } while ((int)(v - target) < 0);
}
__device__ __forceinline__ void flag_peek(uint32_t dst, int f) {
  asm volatile("cp.async.cg.shared.global [%0], [%1], 16;\ncp.async.commit_group;" ::"r"(dst), "l"(g_flag + f * 8) : "memory");
}
__device__ __forceinline__ bool flag_seen(uint32_t src, uint32_t ep1) {
  uint32_t v;
  asm volatile("cp.async.wait_group 0;\nld.shared.u32 %0, [%1];" : "=r"(v) : "r"(src) : "memory");
  return (int)(v - 8 * ep1) >= 0;
}
__device__ __forceinline__ void fence_async_global() { asm volatile("fence.proxy.async.global;" ::: "memory"); }
__device__ __forceinline__ void fence_async_smem() { asm volatile("fence.proxy.async.shared::cta;" ::: "memory"); }
__device__ __forceinline__ void tma2d(uint32_t dst, const CUtensorMap* m, uint32_t bar, int c0, int c1) {
  asm volatile("cp.async.bulk.tensor.2d.shared::cluster.global.mbarrier::complete_tx::bytes [%0], [%1, {%3, %4}], [%2];"
               ::"r"(dst), "l"(m), "r"(bar), "r"(c0), "r"(c1) : "memory");
}
__device__ __forceinline__ void bulk_s2s(uint32_t dst_cl, uint32_t src, uint32_t bytes, uint32_t bar_cl) {
  asm volatile("cp.async.bulk.shared::cluster.shared::cta.mbarrier::complete_tx::bytes [%0], [%1], %2, [%3];" ::"r"(dst_cl), "r"(src), "r"(bytes), "r"(bar_cl) : "memory");
}
__device__ __forceinline__ void map_prefetch(const CUtensorMap* m) { asm volatile("prefetch.tensormap [%0];" ::"l"(m) : "memory"); }
__device__ __forceinline__ void tma2d_mc(uint32_t dst, const CUtensorMap* m, uint32_t bar, int c0, int c1) {
  asm volatile("cp.async.bulk.tensor.2d.shared::cluster.global.mbarrier::complete_tx::bytes.multicast::cluster [%0], [%1, {%3, %4}], [%2], %5;"
               ::"r"(dst), "l"(m), "r"(bar), "r"(c0), "r"(c1), "h"((uint16_t)3) : "memory");
}
__device__ __forceinline__ void tma3d(uint32_t dst, const CUtensorMap* m, uint32_t bar, int c0, int c1, int c2) {
  asm volatile("cp.async.bulk.tensor.3d.shared::cluster.global.mbarrier::complete_tx::bytes [%0], [%1, {%3, %4, %5}], [%2];"
               ::"r"(dst), "l"(m), "r"(bar), "r"(c0), "r"(c1), "r"(c2) : "memory");
}
__device__ __forceinline__ void tma4d(uint32_t dst, const CUtensorMap* m, uint32_t bar, int c0, int c1, int c2, int c3) {
  asm volatile("cp.async.bulk.tensor.4d.shared::cluster.global.mbarrier::complete_tx::bytes [%0], [%1, {%3, %4, %5, %6}], [%2];"
               ::"r"(dst), "l"(m), "r"(bar), "r"(c0), "r"(c1), "r"(c2), "r"(c3) : "memory");
}
__device__ __forceinline__ void tma3d_mc(uint32_t dst, const CUtensorMap* m, uint32_t bar, int c0, int c1, int c2) {
  asm volatile("cp.async.bulk.tensor.3d.shared::cluster.global.mbarrier::complete_tx::bytes.multicast::cluster [%0], [%1, {%3, %4, %5}], [%2], %6;"
               ::"r"(dst), "l"(m), "r"(bar), "r"(c0), "r"(c1), "r"(c2), "h"((uint16_t)3) : "memory");
}
__device__ __forceinline__ void tma3d_prefetch(const CUtensorMap* m, int c0, int c1, int c2) {
  asm volatile("cp.async.bulk.prefetch.tensor.3d.L2.global [%0, {%1, %2, %3}];" ::"l"(m), "r"(c0), "r"(c1), "r"(c2) : "memory");
}
__device__ __forceinline__ void tma2d_st(const CUtensorMap* m, uint32_t src, int c0, int c1) {
  asm volatile("cp.async.bulk.tensor.2d.global.shared::cta.bulk_group [%0, {%2, %3}], [%1];" ::"l"(m), "r"(src), "r"(c0), "r"(c1) : "memory");
}
__device__ __forceinline__ void tma3d_st(const CUtensorMap* m, uint32_t src, int c0, int c1, int c2) {
  asm volatile("cp.async.bulk.tensor.3d.global.shared::cta.bulk_group [%0, {%2, %3, %4}], [%1];" ::"l"(m), "r"(src), "r"(c0), "r"(c1), "r"(c2) : "memory");
}
__device__ __forceinline__ void bulk_commit() { asm volatile("cp.async.bulk.commit_group;" ::: "memory"); }
__device__ __forceinline__ void bulk_wait_read() { asm volatile("cp.async.bulk.wait_group.read 0;" ::: "memory"); }
__device__ __forceinline__ void bulk_wait_all() { asm volatile("cp.async.bulk.wait_group 0;" ::: "memory"); }
__device__ __forceinline__ void wg_fence() { asm volatile("wgmma.fence.sync.aligned;" ::: "memory"); }
__device__ __forceinline__ void wg_commit() { asm volatile("wgmma.commit_group.sync.aligned;" ::: "memory"); }
template <int N> __device__ __forceinline__ void wg_wait() { asm volatile("wgmma.wait_group.sync.aligned %0;" ::"n"(N) : "memory"); }
template <int N> __device__ __forceinline__ void reg_fence(float (&a)[N]) {
#pragma unroll
  for (int i = 0; i < N; i++) asm volatile("" : "+f"(a[i])::"memory");
}
__device__ __forceinline__ void named_sync(int id, int n) { asm volatile("bar.sync %0, %1;" ::"r"(id), "r"(n) : "memory"); }
__device__ __forceinline__ uint32_t pack2(float lo, float hi) { uint32_t r; asm("cvt.rn.bf16x2.f32 %0, %1, %2;" : "=r"(r) : "f"(hi), "f"(lo)); return r; }
__device__ __forceinline__ uint32_t pack2_relu(float lo, float hi) { uint32_t r; asm("cvt.rn.relu.bf16x2.f32 %0, %1, %2;" : "=r"(r) : "f"(hi), "f"(lo)); return r; }
__device__ __forceinline__ float ex2(float x) { float r; asm("ex2.approx.ftz.f32 %0, %1;" : "=f"(r) : "f"(x)); return r; }
__device__ __forceinline__ float rcp(float x) { float r; asm("rcp.approx.ftz.f32 %0, %1;" : "=f"(r) : "f"(x)); return r; }
__device__ __forceinline__ float bf_lo(uint32_t v) { return __uint_as_float(v << 16); }
__device__ __forceinline__ float bf_hi(uint32_t v) { return __uint_as_float(v & 0xFFFF0000u); }
__device__ __forceinline__ uint4 ldcg128(const void* p) { uint4 v; asm volatile("ld.global.cg.v4.b32 {%0, %1, %2, %3}, [%4];" : "=r"(v.x), "=r"(v.y), "=r"(v.z), "=r"(v.w) : "l"(p)); return v; }
__device__ __forceinline__ void stsm4(uint32_t a, uint32_t r0, uint32_t r1, uint32_t r2, uint32_t r3) {
  asm volatile("stmatrix.sync.aligned.m8n8.x4.shared.b16 [%0], {%1, %2, %3, %4};" ::"r"(a), "r"(r0), "r"(r1), "r"(r2), "r"(r3) : "memory");
}
__device__ __forceinline__ void ldsm4(uint32_t a, uint32_t& r0, uint32_t& r1, uint32_t& r2, uint32_t& r3) {
  asm volatile("ldmatrix.sync.aligned.m8n8.x4.shared.b16 {%0, %1, %2, %3}, [%4];" : "=r"(r0), "=r"(r1), "=r"(r2), "=r"(r3) : "r"(a) : "memory");
}
__device__ __forceinline__ uint32_t movm(uint32_t a) { uint32_t d; asm volatile("movmatrix.sync.aligned.m8n8.trans.b16 %0, %1;" : "=r"(d) : "r"(a)); return d; }
__device__ __forceinline__ void mma16(float (&c)[4], uint32_t a0, uint32_t a1, uint32_t a2, uint32_t a3, uint32_t b0, uint32_t b1) {
  asm volatile("mma.sync.aligned.m16n8k16.row.col.f32.bf16.bf16.f32 {%0,%1,%2,%3}, {%4,%5,%6,%7}, {%8,%9}, {%0,%1,%2,%3};"
               : "+f"(c[0]), "+f"(c[1]), "+f"(c[2]), "+f"(c[3]) : "r"(a0), "r"(a1), "r"(a2), "r"(a3), "r"(b0), "r"(b1));
}
__device__ __forceinline__ void mma8(float (&c)[4], uint32_t a0, uint32_t a1, uint32_t b0) {
  asm volatile("mma.sync.aligned.m16n8k8.row.col.f32.bf16.bf16.f32 {%0,%1,%2,%3}, {%4,%5}, {%6}, {%0,%1,%2,%3};"
               : "+f"(c[0]), "+f"(c[1]), "+f"(c[2]), "+f"(c[3]) : "r"(a0), "r"(a1), "r"(b0));
}
__device__ __forceinline__ float2 lds64f(uint32_t a) { float2 v; asm volatile("ld.shared.v2.f32 {%0, %1}, [%2];" : "=f"(v.x), "=f"(v.y) : "r"(a)); return v; }
__device__ __forceinline__ uint4 lds128(uint32_t a) { uint4 v; asm volatile("ld.shared.v4.b32 {%0, %1, %2, %3}, [%4];" : "=r"(v.x), "=r"(v.y), "=r"(v.z), "=r"(v.w) : "r"(a)); return v; }
__device__ __forceinline__ void sts128(uint32_t a, uint32_t x, uint32_t y, uint32_t z, uint32_t w) { asm volatile("st.shared.v4.b32 [%0], {%1, %2, %3, %4};" ::"r"(a), "r"(x), "r"(y), "r"(z), "r"(w) : "memory"); }
__device__ __forceinline__ void sts64f(uint32_t a, float x, float y) { asm volatile("st.shared.v2.f32 [%0], {%1, %2};" ::"r"(a), "f"(x), "f"(y) : "memory"); }
__device__ __forceinline__ float4 lds128f(uint32_t a) { float4 v; asm volatile("ld.shared.v4.f32 {%0, %1, %2, %3}, [%4];" : "=f"(v.x), "=f"(v.y), "=f"(v.z), "=f"(v.w) : "r"(a)); return v; }
__device__ __forceinline__ float lds_bf16(uint32_t a) { uint16_t v; asm volatile("ld.shared.u16 %0, [%1];" : "=h"(v) : "r"(a)); return __uint_as_float((uint32_t)v << 16); }
__device__ __forceinline__ void st_tag2(void* p, float x, float y, uint32_t tag) {
  asm volatile("st.relaxed.gpu.global.v2.b32 [%0], {%1, %2};" ::"l"(p), "r"((__float_as_uint(x) & ~3u) | tag), "r"((__float_as_uint(y) & ~3u) | tag) : "memory");
}
__device__ __forceinline__ float4 ld_tag4(const void* p) { float4 v; asm volatile("ld.relaxed.gpu.global.v4.f32 {%0, %1, %2, %3}, [%4];" : "=f"(v.x), "=f"(v.y), "=f"(v.z), "=f"(v.w) : "l"(p) : "memory"); return v; }
__device__ __forceinline__ uint32_t tag_bad(const float4& v, uint32_t tag) {
  return ((__float_as_uint(v.x) ^ tag) | (__float_as_uint(v.y) ^ tag) | (__float_as_uint(v.z) ^ tag) | (__float_as_uint(v.w) ^ tag)) & 3u;
}

template <int F> __device__ __forceinline__ void wgmma4(float (&d)[64], uint32_t a, uint32_t b) { wgmma4_n128<F>(d, a, b); }
template <int F> __device__ __forceinline__ void wgmma4(float (&d)[96], uint32_t a, uint32_t b) { wgmma4_n192<F>(d, a, b); }
template <int F> __device__ __forceinline__ void wgmma4(float (&d)[128], uint32_t a, uint32_t b) { wgmma4_n256<F>(d, a, b); }

struct Ctx { uint32_t sb, bar, ep1; int i, j, rank; };
template <int PH> struct Geo {
  static constexpr int N0 = PH * 16;
  static constexpr int NS = PH == 5 ? 56 : 16;
  static constexpr int NCH = (PH == 0 || PH == 3) ? 4 : (PH == 4 ? 3 : 2);
  static constexpr int SB = 16384 + NCH * 8192;
  static constexpr int DEPTH = NCH == 2 ? 6 : 4;
  static constexpr int SLOT0 = PH == 0 ? 1 : PH == 1 ? 2 : PH == 3 ? 3 : 0;
  static __device__ __forceinline__ int dep(int m) {
    if (PH == 5 && m >= 5 && m <= M5) return m < M5 ? N0 + m - 5 : -1;
    if (m >= DEPTH || PH == 0 || PH == 2) return N0 + m - DEPTH;
    if (PH == 1) return m == 0 ? 12 : 13 + (m >> 1);
    if (PH == 3) return m == 0 ? N0 - 5 : N0 - 4 + m;
    if (PH == 4) return N0 - 3 + (m < 2 ? m : 2);
    return N0 - 4 + (m < 3 ? m : 3);
  }
  static __device__ __forceinline__ int next(int slot, int m) { return slot + 1 == (PH == 5 && m < M5 - 5 ? 5 : DEPTH) ? 0 : slot + 1; }
  static __device__ __forceinline__ int slot_of(int m) { return PH == 5 ? (m >= M5 - 5 ? (m - M5 + 5) % 6 : m % 5) : (SLOT0 + m) % DEPTH; }
  static __device__ __forceinline__ bool own(int m) { return PH == 2 && EARLY2 ? (m == 0 || m == 3) : (PH == 2 || PH == 3) && m < 2; }
  static __device__ __forceinline__ bool local(int m) { return (PH == 2 || PH == 3) && m < 4; }
  static __device__ __forceinline__ int koff(int m, int j) {
    if (PH == 2 && EARLY2 && m < 4) return (128 * j) ^ (m == 0 ? 0 : m == 1 ? 128 : m == 2 ? 192 : 64);
    if (local(m)) return (128 * j) ^ (64 * m);
    if (PH == 2 || PH == 3) { const int t = m < 10 ? m - 4 : m - 10; return 128 * (t < (j & 6) ? t : t + 2) + (m < 10 ? 0 : 64); }
    if (PH == 5) return m < 32 ? 448 * (m >> 2) + 64 * (m & 3) : 448 * ((m - 32) / 3) + 256 + 64 * ((m - 32) % 3);
    return 64 * m;
  }
};
__device__ __forceinline__ void wait_empty(const Ctx& c, int d) { mbar_wait(c.bar + 8 * (B_EMPTY + (d & 7)), (d >> 3) & 1); }

__device__ __forceinline__ void set_progress(const Ctx& c, int d) { asm volatile("st.volatile.shared.s32 [%0], %1;" ::"r"(c.bar + 8 * B_PEEK + 16), "r"(d) : "memory"); }
__device__ __forceinline__ void wait_progress(const Ctx& c, int d) {
  asm volatile("{\n.reg .pred p;\n.reg .s32 n, v;\nmov.s32 n, 0;\n"
               "W: ld.volatile.shared.s32 v, [%0];\nsetp.ge.s32 p, v, %1;\n@p bra D;\nnanosleep.u32 %3;\n"
               "add.s32 n, n, 1;\nsetp.lt.s32 p, n, %2;\n@p bra W;\ntrap;\nD:\n}\n" ::"r"(c.bar + 8 * B_PEEK + 16), "r"(d), "n"(SPIN_LIMIT), "n"(NSL) : "memory");
}
static_assert(PACE4 + PACE <= M5 - 6, "the first h1 stores must not wait for slot 5");

template <int PH> __device__ __forceinline__ void produce_b(const Params& p, const Ctx& c, int m0, int m1) {
  using G = Geo<PH>;
  int slot = G::slot_of(m0);
#pragma unroll 1
  for (int m = m0; m < m1; m++) {
    const int n = G::N0 + m, d = G::dep(m);
    if (d >= 0) wait_empty(c, d);
    if (PH == 5 && m == M5) { mbar_wait(c.bar + 8 * B_SEMPTY, 1); mbar_wait(c.bar + 8 * (B_SEMPTY + 1), 1); }
    const uint32_t fb = c.bar + 8 * (n & 7), dst = c.sb + slot * G::SB + 16384;
    mbar_expect_tx(fb, G::own(m) ? G::SB - 16384 : G::SB);
    const int k0 = G::koff(m, c.j);
    if (PH == 0 && m < NA0) { tma3d(dst - 16384, &p.mX, fb, k0, 0, 64 * c.i); tma3d(dst - 8192, &p.mX, fb, k0, 1, 64 * c.i); }
    if (PH == 0) tma4d(dst, &p.mWkv, fb, 0, k0, 2 * c.j, 1);
    if (PH == 1) tma3d(dst, &p.mWq, fb, 0, k0, 2 * c.j);
    if (PH == 2) tma3d(dst, &p.mWo, fb, 0, k0, 2 * c.j);
    if (PH == 3) tma3d(dst, &p.mW1a, fb, 0, k0, 7 * c.j);
    if (PH == 4) tma3d(dst, &p.mW1b, fb, 0, k0, 7 * c.j + 4);
    if (PH == 5) tma3d(dst, &p.mW2, fb, 0, k0, 2 * c.j);
    if (d >= 0) set_progress(c, d);
    if (PH == 0 && m == 0) PROF(2);
    if (PH == 5 && m == MPF) map_prefetch(&p.mOut);
    slot = G::next(slot, m);
  }
}
template <int PH> __device__ __forceinline__ void produce_a(const Params& p, const Ctx& c, bool& seen) {
  using G = Geo<PH>;
  constexpr int M1 = PH == 5 ? 32 : PH == 4 ? 16 : 10;
  const int F0 = (PH == 2 ? F_O : PH == 3 ? F_H : F_H1) + c.i * 4 + c.rank;
  int slot = G::SLOT0;
  const int row = 128 * c.i + 64 * c.rank;
#pragma unroll 1
  for (int m = 0; m < G::NS; m++) {
    if (!G::local(m) && (PH > 0 || m >= NA0)) {
      const int n = G::N0 + m, d = G::dep(m);
      if (m == 4 && (PH == 2 || PH == 3)) { flag_wait(F0, 8 * c.ep1); fence_async_global(); PROF(PH == 2 ? 24 : 26); }
      if (d >= 0) wait_empty(c, d);
      if ((m == M1 && PH >= 2 && PH != 4) || (PH == 5 && m == 0)) {
        if (!seen) { if (!flag_seen(c.bar + 8 * B_PEEK, c.ep1)) flag_wait(F0 + (m ? 2 : 0), 8 * c.ep1); fence_async_global(); }
        PROF(PH == 2 ? 25 : PH == 3 ? 29 : 27 + (m >> 5));
      }
      const uint32_t fb = c.bar + 8 * (n & 7), dst = c.sb + slot * G::SB + c.rank * 8192;
      const int k0 = G::koff(m, c.j);
      if (PH <= 1) tma3d_mc(dst, &p.mX, fb, k0, c.rank, 64 * c.i);
      if (PH == 2) tma2d_mc(dst, &p.mO, fb, k0, row);
      if (PH == 3 || PH == 4) tma2d_mc(dst, &p.mH, fb, k0, row);
      if (PH == 5) tma2d_mc(dst, &p.mH1, fb, k0, row);
      if (PH == 0 && m == NA0) PROF(3);
      if (PH >= 2 && (m == M1 - PK0 || m == M1 - 1)) {
        seen = m == M1 - 1 && flag_seen(c.bar + 8 * B_PEEK, c.ep1);
        if (seen) fence_async_global(); else flag_peek(c.bar + 8 * B_PEEK, F0 + (PH == 4 ? 0 : 2));
      }
    }
    slot = G::next(slot, m);
  }
}

struct Con { uint32_t rel, stg, da; int wg, w, lane, spin; bool do_rel; };
template <int PH, bool FIRST> __device__ __forceinline__ void issue(float (&acc)[Geo<PH>::NCH * 32], const Ctx& c, Con& k, int m, int slot) {
  using G = Geo<PH>;
  const int n = G::N0 + m;
  mbar_wait_u(c.bar + 8 * (n & 7), (n >> 3) & 1, k.spin);
  if (m == 0 && k.do_rel) PROF(32 + 32 * k.wg + 3 * PH);
  if (PH == 2 && (m == 4 || m == 10) && k.do_rel) PROF(32 + 32 * k.wg + 19 + (m >> 3));
  if (PH == 3 && (m == 2 || m == 4) && k.do_rel) PROF(32 + 32 * k.wg + 20 + (m >> 1));
  if (PH == 2 && (m == 2 || m == 3 || m == 5) && k.do_rel) PROF(32 + 32 * k.wg + 22 + m);
  if (PH == 3 && (m == 3 || m == 10) && k.do_rel) PROF(32 + 32 * k.wg + 28 + (m >> 3));
  const uint32_t so = slot * (G::SB >> 4);
  wg_fence();
  wgmma4<FIRST>(acc, G::own(m) ? k.da + k.wg * 512 + ((OFF_STG + (m & 1) * 8192) >> 4) : k.da + so, so + (((SMEM_BASE + 16384) >> 4) | (512u << 16)));
  wg_commit();
}
template <int PH> __device__ __forceinline__ void retire(Con& k, int m) {
  wg_wait<1>();
  if (k.do_rel && (PH < 5 || m <= 50)) mbar_arrive_cl(k.rel + 8 * ((Geo<PH>::N0 + m - 1) & 7));
}
template <int PH, int PEND = 0> __device__ __forceinline__ void finish(Con& k) {
  wg_wait<PEND>();
  if (PH < 5 && k.do_rel) mbar_arrive_cl(k.rel + 8 * 7);
  if (k.do_rel) PROF(32 + 32 * k.wg + 3 * PH + 1);
}
template <int PH> __device__ __forceinline__ void steps(float (&acc)[Geo<PH>::NCH * 32], const Ctx& c, Con& k, int m0, int m1) {
  using G = Geo<PH>;
  int slot = G::slot_of(m0);
#pragma unroll 1
  for (int m = m0; m < m1; m++) {
    issue<PH, false>(acc, c, k, m, slot);
    retire<PH>(k, m);
    slot = G::next(slot, m);
  }
}
#define ISSUE(PH, acc, m) issue<PH, false>(acc, c, k, m, Geo<PH>::slot_of(m))
#define ISSUE0(PH, acc) issue<PH, true>(acc, c, k, 0, Geo<PH>::SLOT0)

__device__ __forceinline__ void handoff(const Ctx& c, Con& k, int bar = B_SFULL) {
  fence_async_smem();
  __syncwarp();
  if (k.lane == 0) mbar_arrive(c.bar + 8 * (bar + k.wg));
}

struct Pre { float4 cs[4]; float2 s0, s1; };
template <int PH> __device__ __forceinline__ void pre_load(Pre& a, const Ctx& c, Con& k) {
  if (PH == 0) mbar_wait_u(c.bar + 8 * B_RDY0, 0, k.spin);
  if (PH == 1) { mbar_wait_u(c.bar + 8 * B_RDY1, 0, k.spin); mbar_wait_u(c.bar + 8 * (B_HALO + k.wg), 0, k.spin); }
  if (PH == 4) { mbar_wait_u(c.bar + 8 * B_RDY1, 1, k.spin); mbar_wait_u(c.bar + 8 * (B_SEMPTY + k.wg), 0, k.spin); }
  if (PH == 3) { mbar_wait_u(c.bar + 8 * B_RDY0, 1, k.spin); mbar_wait_u(c.bar + 8 * (B_EMPTY + 4), 1, k.spin); }
  const uint32_t sta = c.sb + OFF_ST + (k.wg * 64 + k.w * 16 + (k.lane >> 2)) * 8;
  a.s0 = lds64f(sta); a.s1 = lds64f(sta + 64);
  a.s0.x = -a.s0.x; a.s1.x = -a.s1.x;
#pragma unroll
  for (int u = 0; u < 4; u++) a.cs[u] = lds128f(c.sb + OFF_CS + (Geo<PH>::NCH == 4 ? 0 : 1024) + (PH == 3 ? u ^ ROT3 : u) * 64 + (k.lane & 3) * 16);
}
template <int PH, int U0, int U1> __device__ __forceinline__ void qkv_pack(uint32_t (&pk)[Geo<PH>::NCH * 8][2], const float (&acc)[Geo<PH>::NCH * 32], Pre& a, const Ctx& c, Con& k) {
  const uint32_t csa = c.sb + OFF_CS + PH * 1024 + (k.lane & 3) * 16;
#pragma unroll
  for (int u = U0; u < U1; u++) {
    const float4 s = a.cs[u & 3];
    if (u + 4 < Geo<PH>::NCH * 4) a.cs[u & 3] = lds128f(csa + (u + 4) * 64);
    float v[8];
#pragma unroll
    for (int e = 0; e < 8; e++) {
      v[e] = fmaf((e & 2) ? a.s1.x : a.s0.x, (e & 4) ? ((e & 1) ? s.w : s.z) : ((e & 1) ? s.y : s.x), acc[8 * u + e]);
      if (PH == 0) v[e] *= (e & 2) ? a.s1.y : a.s0.y;
    }
#pragma unroll
    for (int e = 0; e < 4; e++) pk[2 * u + (e >> 1)][e & 1] = pack2(v[2 * e], v[2 * e + 1]);
  }
}
#define HALO_SRC(kv, H, x) kv[((x) < 8 ? 0 : 8) + 8 * (H) + (x)][1]
template <int H> __device__ __forceinline__ void halo_publish(uint32_t (&kv)[32][2], const Ctx& c, Con& k) {
  if (k.w < 3) {
    const uint32_t ha = k.stg + (k.w + 1) * 2048 + k.lane * 16;
#pragma unroll
    for (int u = 4 * H; u < 4 * H + 4; u++)
      sts128(ha + (u >> 2) * 8192 + (u & 3) * 512, HALO_SRC(kv, u >> 2, 4 * (u & 3)), HALO_SRC(kv, u >> 2, 4 * (u & 3) + 1), HALO_SRC(kv, u >> 2, 4 * (u & 3) + 2), HALO_SRC(kv, u >> 2, 4 * (u & 3) + 3));
    __syncwarp();
    if (H == 1 && k.lane == 0) mbar_arrive(c.bar + 8 * (B_HALO + k.wg));
  } else if (c.i < 15) {
    uint4* hp = g_halo + ((c.i * 8 + c.j) * 2 + k.wg) * 512 + k.lane;
#pragma unroll
    for (int u = 8 * H; u < 8 * H + 8; u++) {
      const unsigned long long x = ((unsigned long long)c.ep1 << 32) | HALO_SRC(kv, u >> 3, 2 * (u & 7)), y = ((unsigned long long)c.ep1 << 32) | HALO_SRC(kv, u >> 3, 2 * (u & 7) + 1);
      asm volatile("st.relaxed.gpu.global.v2.b64 [%0], {%1, %2};" ::"l"(hp + u * 32), "l"(x), "l"(y) : "memory");
    }
  }
}
template <int H> __device__ __forceinline__ void attend(const uint32_t (&q)[16][2], const uint32_t (&kv)[32][2], float sc0, float sc1, float (&o)[8][4], float (&dn)[4], const Ctx& c, Con& k) {
  uint32_t hl[16];
#pragma unroll
  for (int u = 0; u < 4; u++) { const uint4 v = lds128(k.stg + H * 8192 + k.w * 2048 + k.lane * 16 + u * 512); hl[4 * u] = v.x; hl[4 * u + 1] = v.y; hl[4 * u + 2] = v.z; hl[4 * u + 3] = v.w; }
  const bool g0 = 2 * (k.lane & 3) > (k.lane >> 2), g1 = 2 * (k.lane & 3) + 1 > (k.lane >> 2), nohalo = (k.w == 0 && c.i == 0);
  const float L2E = 1.4426950408889634f;
  float sa[2][4], sb[2][4], sh[2][4];
#pragma unroll
  for (int e = 0; e < 8; e++) { sa[e >> 2][e & 3] = 0.f; sb[e >> 2][e & 3] = 0.f; sh[e >> 2][e & 3] = 0.f; }
#pragma unroll
  for (int ks = 0; ks < 2; ks++)
#pragma unroll
    for (int hd = 0; hd < 2; hd++) {
      const int x = 4 * hd + 2 * ks, t = 8 * H + x;
      mma16(sa[hd], q[t][0], q[t][1], q[t + 1][0], q[t + 1][1], kv[t][0], kv[t + 1][0]);
      mma16(sb[hd], q[t][0], q[t][1], q[t + 1][0], q[t + 1][1], kv[t][1], kv[t + 1][1]);
      mma16(sh[hd], q[t][0], q[t][1], q[t + 1][0], q[t + 1][1], hl[x], hl[x + 1]);
    }
  uint32_t vt[8];
#pragma unroll
  for (int t = 0; t < 8; t++) vt[t] = movm(kv[16 + 8 * H + t][0]);
  float l[4][2]; uint32_t pp[4][2];
#pragma unroll
  for (int hd = 0; hd < 2; hd++) {
    l[2 * hd][0] = (g0 ? sh[hd][0] : sa[hd][0]) * sc0; l[2 * hd][1] = (g1 ? sh[hd][1] : sa[hd][1]) * sc0;
    l[2 * hd + 1][0] = (g0 ? sa[hd][2] : sb[hd][2]) * sc1; l[2 * hd + 1][1] = (g1 ? sa[hd][3] : sb[hd][3]) * sc1;
    if (nohalo && g0) l[2 * hd][0] = -1e9f;
    if (nohalo && g1) l[2 * hd][1] = -1e9f;
  }
#pragma unroll
  for (int e = 0; e < 4; e++) dn[e] = fmaxf(l[e][0], l[e][1]);
#pragma unroll
  for (int o = 1; o < 3; o++)
#pragma unroll
    for (int e = 0; e < 4; e++) dn[e] = fmaxf(dn[e], __shfl_xor_sync(~0u, dn[e], o));
#pragma unroll
  for (int e = 0; e < 4; e++) {
    const float x = ex2((l[e][0] - dn[e]) * L2E), y = ex2((l[e][1] - dn[e]) * L2E);
    const uint32_t pr = pack2(x, y), mk = (g0 ? 0xFFFFu : 0u) | (g1 ? 0xFFFF0000u : 0u);
    pp[e][0] = pr & mk; pp[e][1] = pr & ~mk;
    dn[e] = x + y;
  }
#pragma unroll
  for (int t = 0; t < 8; t++) {
    o[t][0] = o[t][1] = o[t][2] = o[t][3] = 0.f;
    mma16(o[t], pp[(t >> 2) * 2][0], 0u, pp[(t >> 2) * 2][1], pp[(t >> 2) * 2 + 1][0], hl[8 + t], vt[t]);
  }
#pragma unroll
  for (int x = 1; x < 3; x++)
#pragma unroll
    for (int e = 0; e < 4; e++) dn[e] += __shfl_xor_sync(~0u, dn[e], x);
#pragma unroll
  for (int t = 0; t < 8; t++) mma8(o[t], 0u, pp[(t >> 2) * 2 + 1][1], kv[16 + 8 * H + t][1]);
#pragma unroll
  for (int e = 0; e < 4; e++) dn[e] = rcp(dn[e]);
}
template <int H> __device__ __forceinline__ void attend_store(const float (&o)[8][4], const float (&dn)[4], const Ctx& c, Con& k) {
  const uint32_t oa = k.stg + H * 8192 + (k.w * 16 + (k.lane & 15)) * 128;
#pragma unroll
  for (int u = 0; u < 4; u++) {
    const float r0 = dn[u & 2], r1 = dn[(u & 2) + 1];
    stsm4(oa + (((2 * u + (k.lane >> 4)) ^ (k.lane & 7)) << 4), pack2(o[2 * u][0] * r0, o[2 * u][1] * r0), pack2(o[2 * u][2] * r1, o[2 * u][3] * r1),
          pack2(o[2 * u + 1][0] * r0, o[2 * u + 1][1] * r0), pack2(o[2 * u + 1][2] * r1, o[2 * u + 1][3] * r1));
  }
  handoff(c, k, H == 0 ? B_SFA : B_SFULL);
}

__device__ __forceinline__ void res_load(uint32_t (&res)[32], uint32_t bar, uint32_t par, Con& k) {
  mbar_wait_u(bar, par, k.spin);
#pragma unroll
  for (int u = 0; u < 8; u++)
    ldsm4(k.stg + (u >> 2) * 8192 + (k.w * 16 + (k.lane & 15)) * 128 + ((((2 * u & 7) + (k.lane >> 4)) ^ (k.lane & 7)) << 4), res[4 * u], res[4 * u + 1], res[4 * u + 2], res[4 * u + 3]);
}
template <int CH> __device__ __forceinline__ void epi_res(const float (&acc)[64], uint32_t (&res)[32], float sc0, float sc1, Con& k) {
  const uint32_t oa = k.stg + CH * 8192 + (k.w * 16 + (k.lane & 15)) * 128;
#pragma unroll
  for (int u = 0; u < 4; u++) {
#pragma unroll
    for (int e = 0; e < 4; e++) {
      const int x = 16 * CH + 4 * u + e;
      const float sc = (e & 1) ? sc1 : sc0;
      res[x] = pack2(fmaf(sc, acc[2 * x], bf_lo(res[x])), fmaf(sc, acc[2 * x + 1], bf_hi(res[x])));
    }
    stsm4(oa + (((2 * u + (k.lane >> 4)) ^ (k.lane & 7)) << 4), res[16 * CH + 4 * u], res[16 * CH + 4 * u + 1], res[16 * CH + 4 * u + 2], res[16 * CH + 4 * u + 3]);
  }
}

template <int NCH, int C0, int C1> __device__ __forceinline__ void epi_ffn1(const float (&acc)[NCH * 32], Pre& a, const Ctx& c, Con& k) {
  const uint32_t csa = c.sb + OFF_CS + (NCH == 4 ? 0 : 1024) + (k.lane & 3) * 16;
  const uint32_t rowo = (k.w * 16 + (k.lane & 15)) * 128;
#pragma unroll
  for (int x = C0; x < C1; x++) {
    const int u = NCH == 4 ? x ^ ROT3 : x, ch = u >> 2, t = 8 * u;
    const uint32_t cb = ch < 2 ? k.stg + ch * 8192 : c.sb + OFF_SPARE + k.wg * 8192 + (ch == NCH - 1 ? 16384 : 0);
    const float4 s = a.cs[u & 3];
    const uint32_t v0 = pack2_relu(fmaf(a.s0.x, s.x, acc[t]), fmaf(a.s0.x, s.y, acc[t + 1])), v1 = pack2_relu(fmaf(a.s1.x, s.x, acc[t + 2]), fmaf(a.s1.x, s.y, acc[t + 3]));
    const uint32_t v2 = pack2_relu(fmaf(a.s0.x, s.z, acc[t + 4]), fmaf(a.s0.x, s.w, acc[t + 5])), v3 = pack2_relu(fmaf(a.s1.x, s.z, acc[t + 6]), fmaf(a.s1.x, s.w, acc[t + 7]));
    if (x + 4 < NCH * 4) a.cs[u & 3] = lds128f(csa + (NCH == 4 ? (x + 4) ^ ROT3 : x + 4) * 64);
    stsm4(cb + rowo + ((((2 * u & 7) + (k.lane >> 4)) ^ (k.lane & 7)) << 4), v0, v1, v2, v3);
  }
  if (C1 == 4 * NCH) handoff(c, k);
}

__device__ __forceinline__ void acc_stat(uint32_t v, float sh, float& s1, float& s2) {
  const float x = bf_lo(v) - sh, y = bf_hi(v) - sh;
  s1 += x + y; s2 = fmaf(y, y, fmaf(x, x, s2));
}
__device__ __forceinline__ float2 row_stat(uint32_t ra, uint32_t xo, float sh) {
  float s1[2] = {0.f, 0.f}, s2[2] = {0.f, 0.f};
  uint4 v[2][2];
#pragma unroll
  for (int e = 0; e < 2; e++) v[0][e] = lds128(ra + ((e * 16) ^ xo));
#pragma unroll 1
  for (int b = 0; b < 4; b++) {
#pragma unroll
    for (int h = 0; h < 2; h++) {
      const int n = (2 * b + h + 1) & 7;
#pragma unroll
      for (int e = 0; e < 2; e++) v[h ^ 1][e] = lds128(ra + (n >> 2) * 8192 + (((n & 3) * 32 + e * 16) ^ xo));
#pragma unroll
      for (int e = 0; e < 2; e++) { acc_stat(v[h][e].x, sh, s1[0], s2[0]); acc_stat(v[h][e].y, sh, s1[1], s2[1]); acc_stat(v[h][e].z, sh, s1[0], s2[0]); acc_stat(v[h][e].w, sh, s1[1], s2[1]); }
    }
  }
  return make_float2(s1[0] + s1[1], s2[0] + s2[1]);
}
template <bool PF> __device__ __forceinline__ void unit_load(const Params& p, int j, int u, uint32_t dst, uint32_t bar) {
  const int ch = u >> 3;
  const CUtensorMap* mp = ch < 6 ? &p.mCq : &p.mC1;
  const int col = ch < 6 ? (ch < 4 ? 1024 + (ch >> 1) * 1024 : 0) + 128 * j + 64 * (ch & 1) : 448 * j + 64 * (ch - 6);
  if (PF) {
    asm volatile("cp.async.bulk.prefetch.tensor.2d.L2.global [%0, {%1, %2}];" ::"l"(mp), "r"(col), "r"((u & 7) * 128) : "memory");
  } else {
    mbar_expect_tx(bar, 16384);
    tma2d(dst, mp, bar, col, (u & 7) * 128);
  }
}
__device__ __forceinline__ void unit_sum(int j, uint32_t tag, int u, uint32_t src, int lane) {
  float s[8];
#pragma unroll
  for (int e = 0; e < 8; e++) s[e] = 0.f;
  uint4 v[2][4];
#pragma unroll
  for (int e = 0; e < 4; e++) v[0][e] = lds128(src + e * 512 + lane * 16);
#pragma unroll 1
  for (int b = 0; b < 4; b++) {
#pragma unroll
    for (int h = 0; h < 2; h++) {
#pragma unroll
      for (int e = 0; e < 4; e++) v[h ^ 1][e] = lds128(src + ((2 * b + h + 1) & 7) * 2048 + e * 512 + lane * 16);
#pragma unroll
      for (int e = 0; e < 4; e++) {
        const uint4 t = v[h][e];
        s[0] += bf_lo(t.x); s[1] += bf_hi(t.x); s[2] += bf_lo(t.y); s[3] += bf_hi(t.y);
        s[4] += bf_lo(t.z); s[5] += bf_hi(t.z); s[6] += bf_lo(t.w); s[7] += bf_hi(t.w);
      }
    }
  }
  const bool hi = lane & 16, md = lane & 8;
#pragma unroll
  for (int e = 0; e < 4; e++) s[e] = (hi ? s[e + 4] : s[e]) + __shfl_xor_sync(~0u, hi ? s[e] : s[e + 4], 16);
#pragma unroll
  for (int e = 0; e < 2; e++) s[e] = (md ? s[e + 2] : s[e]) + __shfl_xor_sync(~0u, md ? s[e] : s[e + 2], 8);
  st_tag2(g_cs + ((u & 7) * 8 + j) * 832 + (u >> 3) * 64 + (lane & 7) * 8 + (lane >> 4) * 4 + (md ? 2 : 0), s[0], s[1], tag);
}
__device__ __forceinline__ void cs_gather(const Ctx& c, int col, int dcol) {
  float4 v[8]; uint32_t bad; int it = 0;
  do {
    bad = 0;
#pragma unroll
    for (int u = 0; u < 8; u++) v[u] = ld_tag4(g_cs + (u * 8 + c.j) * 832 + col);
#pragma unroll
    for (int u = 0; u < 8; u++) bad |= tag_bad(v[u], c.ep1);
    spin_check(it);
  } while (bad);
#pragma unroll
  for (int u = 1; u < 8; u++) { v[0].x += v[u].x; v[0].y += v[u].y; v[0].z += v[u].z; v[0].w += v[u].w; }
  const uint32_t da = c.sb + OFF_CS + (dcol >> 4) * 64 + (dcol & 4) * 8 + (dcol & 8);
  sts64f(da, v[0].x, v[0].y); sts64f(da + 16, v[0].z, v[0].w);
}
__device__ __forceinline__ void halo_relay(const Ctx& c, int T, int a, int lane) {
  uint32_t hl[16];
#pragma unroll
  for (int u = 0; u < 16; u++) hl[u] = 0;
  if (c.i > 0) {
    const uint4* hp = g_halo + ((((c.i - 1) * 8 + c.j) * 2 + a) * 2 + T) * 256 + lane;
    int it = 0; bool ok;
    do {
      ok = true;
#pragma unroll
      for (int u = 0; u < 8; u++) {
        unsigned long long x, y;
        asm volatile("ld.relaxed.gpu.global.v2.b64 {%0, %1}, [%2];" : "=l"(x), "=l"(y) : "l"(hp + u * 32) : "memory");
        hl[2 * u] = (uint32_t)x; hl[2 * u + 1] = (uint32_t)y;
        ok = ok && (uint32_t)(x >> 32) == c.ep1 && (uint32_t)(y >> 32) == c.ep1;
      }
      spin_check(it);
    } while (!ok);
  }
#pragma unroll
  for (int u = 0; u < 4; u++) sts128(c.sb + OFF_STG + a * 16384 + T * 8192 + lane * 16 + u * 512, hl[4 * u], hl[4 * u + 1], hl[4 * u + 2], hl[4 * u + 3]);
}

__device__ __forceinline__ void aux_warp(const Params& p, const Ctx& c, int a, int lane) {
  const uint32_t spare = c.sb + OFF_SPARE, mystg = c.sb + OFF_STG + a * 16384;
  const uint32_t bA = c.bar + 8 * (B_AUX + a), bSF = c.bar + 8 * (B_SFULL + a), bSE = c.bar + 8 * (B_SEMPTY + a);
  const bool lead = (a == 0 && lane == 0);
  const int row0 = 128 * c.i + 64 * a, u0 = 2 * c.i + a;
  const uint32_t tag = c.ep1 & 3, peer = mapa(c.sb, c.rank ^ 1);
  if (lane == 0) {
    if (a == 0) {
      wait_progress(c, 0);
#pragma unroll
      for (int s = 2; s < 13; s++) map_prefetch(&p.mX + s);
    }
    wait_progress(c, AUX_GATE);
    unit_load<false>(p, c.j, u0, mystg, bA);
  }
  mbar_wait(bA, 0);
  if (lead) PROF(4);
  unit_sum(c.j, tag, u0, mystg, lane);
  if (lead) PROF(6);
  wait_progress(c, G0);
  if (XL == 0) {
    float4 v; int it = 0;
    do { v = ld_tag4(g_xst + row0 + 2 * lane); spin_check(it); } while (tag_bad(v, tag));
    sts128(c.sb + OFF_ST + (64 * a + 2 * lane) * 8, __float_as_uint(v.x), __float_as_uint(v.y), __float_as_uint(v.z), __float_as_uint(v.w));
  } else {
    float4 v; int it = 0;
    do { v = ld_tag4(g_xst + (64 * c.i + 32 * a + lane) * 4); spin_check(it); } while (tag_bad(v, tag));
    sts64f(c.sb + OFF_ST + (32 * a + lane) * 8, v.x, v.y); sts64f(c.sb + OFF_ST + (64 + 32 * a + lane) * 8, v.z, v.w);
  }
#pragma unroll 1
  for (int r = 0; r < 4; r++) {
    if (r == 2) {
      if (lane == 0) {
        mbar_wait(c.bar + 8 * (B_SFA + a), 1);
        tma2d_st(&p.mH, mystg, 128 * c.j, row0); bulk_commit();
        if (lead) PROF(18);
        wait_empty(c, 46);
        bulk_s2s(peer + 1 * 49152 + a * 8192, mystg, 8192, peer + OFF_BAR + 8 * (50 & 7));
        if (HORD == 0) { bulk_wait_all(); flag_add(F_H + c.i * 4 + a); if (lead) PROF(19); }
        mbar_wait(bSF, 1);
        wait_empty(c, 47);
        bulk_s2s(peer + 2 * 49152 + a * 8192, mystg + 8192, 8192, peer + OFF_BAR + 8 * (51 & 7));
        if (HORD == 1) { bulk_wait_all(); flag_add(F_H + c.i * 4 + a); if (lead) PROF(19); }
        wait_progress(c, 48 + PACEH + a);
        tma2d_st(&p.mH, mystg + 8192, 128 * c.j + 64, row0); bulk_commit();
        bulk_wait_all(); flag_add(F_H + c.i * 4 + 2 + a);
        if (lead) PROF(20);
      }
      __syncwarp();
#pragma unroll 1
      for (int hh = 0; hh < 2; hh++) {
        const int rr = lane + 32 * hh;
        const uint32_t ra = mystg + rr * 128;
        const float sh = lds_bf16(ra);
        const float2 st = row_stat(ra, (lane & 7) << 4, sh);
        const float lm = st.x * (1.f / 128);
        st_tag2(g_hst + row0 * 8 + c.j * 64 + rr, sh + lm, fmaf(-st.x, lm, st.y), tag);
      }
      __syncwarp();
      if (lane == 0) mbar_arrive(bSE);
      if (lead) PROF(12);
      wait_progress(c, GS);
      {
        float4 v[8]; uint32_t bad; int it = 0;
        do {
          bad = 0;
#pragma unroll
          for (int u = 0; u < 8; u++) v[u] = ld_tag4(g_hst + row0 * 8 + u * 64 + 2 * lane);
#pragma unroll
          for (int u = 0; u < 8; u++) bad |= tag_bad(v[u], tag);
          spin_check(it);
        } while (bad);
        float m0 = 0.f, m1 = 0.f, q0 = 0.f, q1 = 0.f;
#pragma unroll
        for (int u = 0; u < 8; u++) { m0 += v[u].x; m1 += v[u].z; }
        m0 *= 0.125f; m1 *= 0.125f;
#pragma unroll
        for (int u = 0; u < 8; u++) { q0 += fmaf(128.f * (v[u].x - m0), v[u].x - m0, v[u].y); q1 += fmaf(128.f * (v[u].z - m1), v[u].z - m1, v[u].w); }
        sts128(c.sb + OFF_ST + (64 * a + 2 * lane) * 8, __float_as_uint(m0), __float_as_uint(rsqrtf(fmaxf(q0, 0.f) * (1.f / D_) + 1e-5f)),
               __float_as_uint(m1), __float_as_uint(rsqrtf(fmaxf(q1, 0.f) * (1.f / D_) + 1e-5f)));
      }
    }
    const int nl = r == 1 ? 16 : r == 3 ? 24 : 32, dcol = 256 * (r & 1) + 4 * (nl * a + lane);
    if (lane < nl) cs_gather(c, dcol + 384 * (r >> 1), dcol);
    __syncwarp();
    if (lane == 0) { mbar_arrive(c.bar + 8 * (B_RDY0 + (r & 1))); if (lead) PROF(7 + r); }
    if (r == 1) {
      wait_progress(c, GH);
#pragma unroll 1
      for (int t = 0; t < 2; t++) halo_relay(c, t, a, lane);
      __syncwarp();
      if (lane == 0) {
        mbar_arrive(c.bar + 8 * (B_HALO + a));
        if (lead) PROF(11);
#pragma unroll 1
        for (int t = 0; t < 2; t++) {
          mbar_wait(t ? bSF : c.bar + 8 * (B_SFA + a), 0);
          tma2d_st(&p.mO, mystg + t * 8192, 128 * c.j + 64 * t, row0); bulk_commit();
          if (lead) PROF(13 + 3 * t);
          wait_empty(c, 28 - EARLY2 + t);
          bulk_s2s(peer + (2 - EARLY2 + t) * 32768 + a * 8192, mystg + t * 8192, 8192, peer + OFF_BAR + 8 * (2 - EARLY2 + t));
          bulk_wait_all(); flag_add(F_O + c.i * 4 + 2 * t + a);
          if (lead) PROF(14 + 3 * t);
        }
        wait_progress(c, 35);
        mbar_expect_tx(bSE, 16384);
        tma3d(mystg, &p.mX, bSE, 128 * c.j, a, 64 * c.i); tma3d(mystg + 8192, &p.mX, bSE, 128 * c.j + 64, a, 64 * c.i);
      }
      named_sync(3, 64);
    }
    if (r >= 2) {
      if (lane == 0) {
        const int col = 448 * c.j + 256 * (r - 2);
        mbar_wait(bSF, r & 1);
#pragma unroll 1
        for (int x = r - 2; x < 4; x++) {
          wait_progress(c, r == 2 ? 64 + PACE3 + 2 * x + a : 80 + PACE4 + PACE * (2 * (x - 1) + a));
          tma2d_st(&p.mH1, x < 2 ? spare + x * 16384 + a * 8192 : mystg + (x - 2) * 8192, col + (x < 2 ? (x + 4 - r) * 64 : (x - 2) * 64), row0);
          bulk_commit();
          if (x == 7 - 2 * r) { bulk_wait_read(); mbar_arrive(bSE); }
        }
        bulk_wait_all(); flag_add(F_H1 + c.i * 4 + 2 * (r - 2) + a);
        if (lead) PROF(20 + r);
        if (r == 3) { mbar_expect_tx(bA, 16384); tma2d(mystg, &p.mH, bA, 128 * c.j, row0); tma2d(mystg + 8192, &p.mH, bA, 128 * c.j + 64, row0); }
      }
      __syncwarp();
    }
  }
}

__device__ __forceinline__ void helper_unit(int g, int& j, int& u) {
  const int x = g >> 3;
  j = x < 16 ? x >> 1 : x < 48 ? (x - 16) >> 2 : (x - 48) / 3;
  u = 8 * (x < 16 ? 4 + (x & 1) : x < 48 ? 6 + (x & 3) : 10 + x % 3) + (g & 7);
}
__device__ __forceinline__ void helper_warp(const Params& p, const Ctx& c, int g0, int warp, int lane) {
  const uint32_t buf = c.sb + warp * 16384, bar = c.bar + 8 * (warp < 8 ? warp : warp + B_SEMPTY - 8);
#pragma unroll 1
  for (int t = 0; t < 12; t++) {
    int j, u;
    if (t < 11 && lane == 0) { helper_unit(g0 + 48 * t + 48, j, u); unit_load<true>(p, j, u, 0, 0); }
    helper_unit(g0 + 48 * t, j, u);
    if (lane == 0) unit_load<false>(p, j, u, buf, bar);
    mbar_wait(bar, t & 1);
    unit_sum(j, c.ep1 & 3, u, buf, lane);
  }
  if (HPF2 && lane == 0) for (int x = g0; x < 448; x += 48) tma3d_prefetch(&p.mW2, 0, Geo<5>::koff(x >> 3, 0), 2 * (x & 7));
}

__device__ __forceinline__ uint32_t load_epoch() {
  uint32_t ctr;
  asm volatile("ld.relaxed.gpu.global.u32 %0, [%1];" : "=r"(ctr) : "l"(&g_ctr) : "memory");
  return (ctr >> 7) + 1;
}

__global__ void __cluster_dims__(2, 1, 1) __launch_bounds__(384, 1) fused_block_kernel(const __grid_constant__ Params p) {
  extern __shared__ __align__(1024) uint8_t smem_raw[];
  Ctx c;
  c.sb = (uint32_t)__cvta_generic_to_shared(smem_raw);
  c.bar = c.sb + OFF_BAR;
  c.rank = blockIdx.x & 1;
  int cl = (blockIdx.x >> 1) + (gridDim.x == 4 ? 64 : 0);
  if (LAYOUT && gridDim.x == 132) {
    uint32_t t; asm("mov.u32 %0, %%smid;" : "=r"(t));
    t >>= 1;
    cl = t < 32 ? (t & 7) * 8 + (t >> 3) : t < 60 ? (1 + (t - 32) % 7) * 8 + 4 + (t - 32) / 7 : t < 62 ? t + 4 : t - 58;
  }
  const bool helper = cl >= 64;
  if (LAYOUT == 0) { c.i = cl & 15; c.j = (cl >> 4) * 2 + c.rank; }
  if (LAYOUT == 1) { c.i = ((cl >> 4) & 3) * 4 + (cl & 3); c.j = ((cl >> 2) & 3) * 2 + c.rank; }
  if (LAYOUT == 2) { c.i = (cl >> 2) & 15; c.j = (cl & 3) * 2 + c.rank; }
  if (LAYOUT == 3) { c.i = cl & 15; c.j = ((cl >> 4) & 3) * 2 + c.rank; }
  const int warp = __shfl_sync(~0u, threadIdx.x >> 5, 0), lane = threadIdx.x & 31;
  if (warp < 2 * PFN && !helper) {
    const bf16* q = (warp & 1) ? p.w + (size_t)(128 * (warp >> 1) + 8 * c.i + (lane >> 2)) * (3 * D_) + D_ + (lane & 2) * 512 + 128 * c.j + 64 * (lane & 1)
                               : p.x + (size_t)(128 * c.i + 16 * c.j + (lane >> 1)) * D_ + 128 * (warp >> 1) + 64 * (lane & 1);
    asm volatile("prefetch.global.L2 [%0];" ::"l"(q));
  }
  if (warp == 8 && lane == 0) {
    PROF(0);
    map_prefetch(&p.mWkv); map_prefetch(&p.mX);
#pragma unroll
    for (int s = 0; s < 4; s++) mbar_init(c.bar + 8 * s, 1);
    fence_async_smem();
    if (!helper) produce_b<0>(p, c, 0, NB0);
    asm volatile("fence.mbarrier_init.release.cluster;" ::: "memory");
  }
  if (warp == 9 && lane == 0) {
    asm volatile("{\n.reg .pred p;\nsetp.ne.u32 p, %0, %1;\n@p trap;\n}\n" ::"r"(c.sb & 0x3FFFF), "n"(SMEM_BASE));
#pragma unroll
    for (int s = 4; s < B_NUM; s++) mbar_init(c.bar + 8 * s, (s < B_EMPTY || s >= B_SEMPTY) ? 1 : (s >= B_RDY0 ? 2 : 4));
    set_progress(c, -1); __threadfence_block();
    asm volatile("fence.mbarrier_init.release.cluster;" ::: "memory");
    fence_async_smem();
  }
  __syncwarp();
  asm volatile("barrier.cluster.arrive.relaxed.aligned;" ::: "memory");
  asm volatile("barrier.cluster.wait.acquire.aligned;" ::: "memory");
  if (helper) {
    c.ep1 = load_epoch();
    if (HDLY) __nanosleep(HDLY);
    helper_warp(p, c, ((cl & 1) * 2 + c.rank) * 12 + warp, warp, lane);
  } else if (warp >= 8) {
    asm volatile("setmaxnreg.dec.sync.aligned.u32 88;");
    if (warp == 8) {
      if (lane == 0) {
        PROF(1);
        produce_b<0>(p, c, NB0, 16); produce_b<1>(p, c, 0, 16); produce_b<2>(p, c, 0, 16); produce_b<3>(p, c, 0, 16); produce_b<4>(p, c, 0, 16); produce_b<5>(p, c, 0, 56);
        asm volatile("red.relaxed.gpu.global.add.u32 [%0], 1;" ::"l"(&g_ctr) : "memory");
      }
    } else if (warp == 9) {
      if (lane == 0) {
        bool seen = false;
        produce_a<0>(p, c, seen); c.ep1 = load_epoch(); produce_a<1>(p, c, seen); produce_a<2>(p, c, seen); produce_a<3>(p, c, seen); produce_a<4>(p, c, seen); produce_a<5>(p, c, seen);
      }
    } else {
      c.ep1 = load_epoch();
      aux_warp(p, c, warp - 10, lane);
    }
  } else {
    asm volatile("setmaxnreg.inc.sync.aligned.u32 208;");
    c.ep1 = load_epoch();
    Con k;
    k.wg = warp >> 2; k.w = warp & 3; k.lane = lane; k.spin = 0;
    k.do_rel = (threadIdx.x & 127) < 2;
    k.rel = mapa(c.bar + 8 * B_EMPTY, threadIdx.x & 1);
    k.stg = c.sb + OFF_STG + k.wg * 16384;
    k.da = ((SMEM_BASE >> 4) | (1u << 16)) + k.wg * 512;
    uint32_t kv[32][2]; float accq[64], acco[64];
    {
      float acc[128]; Pre pr;
      const int rb = 16 * c.j + 2 * warp + (lane >> 4);
      const uint4* xr = reinterpret_cast<const uint4*>(p.x + (size_t)(128 * c.i + rb) * D_) + (lane & 15);
      uint4 xv[8];
      if (XLD_EARLY) {
#pragma unroll
        for (int e = 0; e < 8; e++) xv[e] = ldcg128(xr + 16 * e);
      }
      ISSUE0(0, acc);
      if (!XLD_EARLY) {
#pragma unroll
        for (int e = 0; e < 8; e++) xv[e] = ldcg128(xr + 16 * e);
      }
      steps<0>(acc, c, k, 1, XST);
      ISSUE(0, acc, XST);
      const float sh = __shfl_sync(~0u, bf_lo(xv[0].x), lane & 16);
      float s1[2] = {0.f, 0.f}, s2[2] = {0.f, 0.f};
#pragma unroll
      for (int e = 0; e < 8; e++) {
        { acc_stat(xv[e].x, sh, s1[0], s2[0]); acc_stat(xv[e].y, sh, s1[1], s2[1]); acc_stat(xv[e].z, sh, s1[0], s2[0]); acc_stat(xv[e].w, sh, s1[1], s2[1]); }
        if (e == 4) { asm volatile("" : "+f"(s1[0]), "+f"(s1[1]), "+f"(s2[0]), "+f"(s2[1])); retire<0>(k, XST); ISSUE(0, acc, XST + 1); }
      }
      float t1 = s1[0] + s1[1], t2 = s2[0] + s2[1];
#pragma unroll
      for (int o = 1; o < 16; o <<= 1) { t1 += __shfl_xor_sync(~0u, t1, o); t2 += __shfl_xor_sync(~0u, t2, o); }
      t1 *= 1.f / D_;
      if ((lane & 15) <= XL) st_tag2(XL ? g_xst + (64 * c.i + (rb >> 1)) * 4 + 2 * (lane & 1) + (rb & 1) : g_xst + 128 * c.i + 64 * (rb & 1) + (rb >> 1), sh + t1, rsqrtf(fmaxf(fmaf(-t1, t1, t2 * (1.f / D_)), 0.f) + 1e-5f), c.ep1 & 3);
      if (threadIdx.x == 0) PROF(5);
      retire<0>(k, XST + 1);
      steps<0>(acc, c, k, XST + 2, 15);
      ISSUE(0, acc, 15); pre_load<0>(pr, c, k); retire<0>(k, 15);
      finish<0>(k);
      qkv_pack<0, 0, SH0 ? 8 : 16>(kv, acc, pr, c, k);
      ISSUE0(1, accq);
      if (SH0) {
        qkv_pack<0, 8, 10>(kv, acc, pr, c, k);
        ISSUE(1, accq, 1); qkv_pack<0, 10, 12>(kv, acc, pr, c, k); retire<1>(k, 1);
        ISSUE(1, accq, 2); qkv_pack<0, 12, 14>(kv, acc, pr, c, k); retire<1>(k, 2);
        ISSUE(1, accq, 3); qkv_pack<0, 14, 16>(kv, acc, pr, c, k); retire<1>(k, 3);
      }
      if (k.do_rel) PROF(32 + 32 * k.wg + 2);
    }
    {
      float (&acc)[64] = accq; Pre pr; uint32_t q[16][2];
      constexpr int M = 1 + 3 * SH0;
      ISSUE(1, acc, M);
#pragma unroll
      for (int t = 16; t < 32; t++) kv[t][1] = movm(kv[t][1]);
      retire<1>(k, M);
      ISSUE(1, acc, M + 1); halo_publish<0>(kv, c, k); retire<1>(k, M + 1);
      ISSUE(1, acc, M + 2); halo_publish<1>(kv, c, k); retire<1>(k, M + 2);
      steps<1>(acc, c, k, M + 3, 15);
      ISSUE(1, acc, 15); pre_load<1>(pr, c, k); retire<1>(k, 15);
      finish<1>(k);
      const float sc0 = pr.s0.y * 0.17677669529663687f, sc1 = pr.s1.y * 0.17677669529663687f;
      qkv_pack<1, 0, 4>(q, acc, pr, c, k);
      float o[8][4], dn[4];
      attend<0>(q, kv, sc0, sc1, o, dn, c, k); attend_store<0>(o, dn, c, k);
      if (k.do_rel) PROF(32 + 32 * k.wg + 23);
      qkv_pack<1, 4, 8>(q, acc, pr, c, k);
      attend<1>(q, kv, sc0, sc1, o, dn, c, k);
      if (EARLY2) {
        mbar_wait_u(c.bar + 8 * (B_SFA + k.wg), 0, k.spin);
        ISSUE0(2, acco);
        if (EARLY2B) ISSUE(2, acco, 1);
      }
      attend_store<1>(o, dn, c, k);
      if (k.do_rel) PROF(32 + 32 * k.wg + 5);
      if (EARLY2 && !EARLY2B) ISSUE(2, acco, 1);
      mbar_wait_u(c.bar + 8 * (B_SFULL + k.wg), 0, k.spin);
    }
    {
      float (&acc)[64] = acco; uint32_t res[32];
      if (EARLY2) retire<2>(k, 1); else ISSUE0(2, acc);
      steps<2>(acc, c, k, 1 + EARLY2, 15);
      ISSUE(2, acc, 15);
      res_load(res, c.bar + 8 * (B_SEMPTY + k.wg), 0, k);
      retire<2>(k, 15);
      finish<2>(k);
      epi_res<0>(acc, res, 1.f, 1.f, k);
      handoff(c, k, B_SFA);
      if (HFEN) reg_fence(acc);
      epi_res<1>(acc, res, 1.f, 1.f, k);
      handoff(c, k);
      if (k.do_rel) PROF(32 + 32 * k.wg + 8);
      mbar_wait_u(c.bar + 8 * (B_SFULL + k.wg), 1, k.spin);
    }
    {
      float acc4[96], acc[64]; Pre pr;
      {
        float acc3[128];
        ISSUE0(3, acc3);
        steps<3>(acc3, c, k, 1, 15);
        ISSUE(3, acc3, 15); pre_load<3>(pr, c, k); retire<3>(k, 15);
        finish<3>(k);
        if (SH3) {
          epi_ffn1<4, 0, 8>(acc3, pr, c, k);
          ISSUE0(4, acc4); epi_ffn1<4, 8, 10>(acc3, pr, c, k);
          ISSUE(4, acc4, 1); epi_ffn1<4, 10, 13>(acc3, pr, c, k); retire<4>(k, 1);
          ISSUE(4, acc4, 2); epi_ffn1<4, 13, 16>(acc3, pr, c, k); retire<4>(k, 2);
        } else {
          epi_ffn1<4, 0, 16>(acc3, pr, c, k);
          ISSUE0(4, acc4);
        }
        if (k.do_rel) PROF(32 + 32 * k.wg + 11);
      }
      steps<4>(acc4, c, k, SH3 ? 3 : 1, 15);
      ISSUE(4, acc4, 15); pre_load<4>(pr, c, k); retire<4>(k, 15);
      if (SH4) {
        ISSUE0(5, acc);
        finish<4, 1>(k);
        reg_fence(acc4);
        ISSUE(5, acc, 1); epi_ffn1<3, 0, 2>(acc4, pr, c, k); retire<5>(k, 1);
        ISSUE(5, acc, 2); epi_ffn1<3, 2, 4>(acc4, pr, c, k); retire<5>(k, 2);
        ISSUE(5, acc, 3); epi_ffn1<3, 4, 6>(acc4, pr, c, k); retire<5>(k, 3);
        ISSUE(5, acc, 4); epi_ffn1<3, 6, 8>(acc4, pr, c, k); retire<5>(k, 4);
        ISSUE(5, acc, 5); epi_ffn1<3, 8, 10>(acc4, pr, c, k); retire<5>(k, 5);
        ISSUE(5, acc, 6); epi_ffn1<3, 10, 12>(acc4, pr, c, k); retire<5>(k, 6);
      } else {
        finish<4>(k);
        epi_ffn1<3, 0, 12>(acc4, pr, c, k);
        ISSUE0(5, acc);
      }
      if (k.do_rel) PROF(32 + 32 * k.wg + 14);
      steps<5>(acc, c, k, SH4 ? 7 : 1, 55);
      ISSUE(5, acc, 55);
      const uint32_t sta = c.sb + OFF_ST + (k.wg * 64 + k.w * 16 + (lane >> 2)) * 8;
      const float sc0 = lds64f(sta).y, sc1 = lds64f(sta + 64).y;
      uint32_t res[32];
      res_load(res, c.bar + 8 * (B_AUX + k.wg), 1, k);
      spin_check(k.spin);
      finish<5>(k);
      epi_res<0>(acc, res, sc0, sc1, k);
      fence_async_smem(); __syncwarp();
      if (lane == 0) tma3d_st(&p.mOut, k.stg + k.w * 2048, 128 * c.j, k.wg, 64 * c.i + 16 * k.w);
      epi_res<1>(acc, res, sc0, sc1, k);
      fence_async_smem(); __syncwarp();
      if (k.do_rel) PROF(32 + 32 * k.wg + 17);
      if (lane == 0) { tma3d_st(&p.mOut, k.stg + 8192 + k.w * 2048, 128 * c.j + 64, k.wg, 64 * c.i + 16 * k.w); bulk_commit(); bulk_wait_read(); }
      if (k.do_rel) PROF(32 + 32 * k.wg + 18);
    }
  }
}

typedef CUresult (*EncFn)(CUtensorMap*, CUtensorMapDataType, cuuint32_t, void*, const cuuint64_t*, const cuuint64_t*, const cuuint32_t*,
                          const cuuint32_t*, CUtensorMapInterleave, CUtensorMapSwizzle, CUtensorMapL2promotion, CUtensorMapFloatOOBfill);

void enc(EncFn f, CUtensorMap* m, const void* ptr, int rank, cuuint64_t d0, cuuint64_t d1, cuuint64_t d2, cuuint64_t s1, cuuint64_t s2,
         cuuint32_t b0, cuuint32_t b1, cuuint32_t b2, CUtensorMapSwizzle sw = CU_TENSOR_MAP_SWIZZLE_128B) {
  const cuuint64_t dims[3] = {d0, d1, d2}, str[2] = {s1, s2};
  const cuuint32_t box[3] = {b0, b1, b2}, es[3] = {1, 1, 1};
  f(m, CU_TENSOR_MAP_DATA_TYPE_BFLOAT16, rank, const_cast<void*>(ptr), dims, str, box, es, CU_TENSOR_MAP_INTERLEAVE_NONE,
    sw, CU_TENSOR_MAP_L2_PROMOTION_L2_256B, CU_TENSOR_MAP_FLOAT_OOB_FILL_NONE);
}

}

extern "C" void kernel_launch(void* const* d_in, const int* in_sizes, int n_in, void* d_out, int out_size) {
  (void)in_sizes; (void)n_in; (void)out_size;
  const void *x = d_in[0], *wqkv = d_in[1], *wo = d_in[2], *w1 = d_in[4], *w2 = d_in[5];
  EncFn f = nullptr;
  cudaDriverEntryPointQueryResult qr;
  cudaGetDriverEntryPoint("cuTensorMapEncodeTiled", (void**)&f, cudaEnableDefault, &qr);
  void *po, *ph, *ph1;
  cudaGetSymbolAddress(&po, g_o); cudaGetSymbolAddress(&ph, g_h); cudaGetSymbolAddress(&ph1, g_h1);
  Params p;
  enc(f, &p.mX, x, 3, D_, 2, S_ / 2, D_ * 2, D_ * 4, 64, 1, 64);
  enc(f, &p.mOut, d_out, 3, D_, 2, S_ / 2, D_ * 2, D_ * 4, 64, 1, 16);
  enc(f, &p.mCq, wqkv, 2, 3 * D_, D_, 1, 3 * D_ * 2, 0, 64, 128, 1, CU_TENSOR_MAP_SWIZZLE_NONE);
  enc(f, &p.mC1, w1, 2, F_, D_, 1, F_ * 2, 0, 64, 128, 1, CU_TENSOR_MAP_SWIZZLE_NONE);
  {
    const cuuint64_t dims[4] = {64, D_, D_ / 64, 3}, str[3] = {3 * D_ * 2, 128, D_ * 2};
    const cuuint32_t box[4] = {64, 64, 2, 2}, es[4] = {1, 1, 1, 1};
    f(&p.mWkv, CU_TENSOR_MAP_DATA_TYPE_BFLOAT16, 4, const_cast<void*>(wqkv), dims, str, box, es, CU_TENSOR_MAP_INTERLEAVE_NONE,
      CU_TENSOR_MAP_SWIZZLE_128B, CU_TENSOR_MAP_L2_PROMOTION_L2_256B, CU_TENSOR_MAP_FLOAT_OOB_FILL_NONE);
  }
  enc(f, &p.mWq, wqkv, 3, 64, D_, D_ / 64, 3 * D_ * 2, 128, 64, 64, 2);
  enc(f, &p.mWo, wo, 3, 64, D_, D_ / 64, D_ * 2, 128, 64, 64, 2);
  enc(f, &p.mW1a, w1, 3, 64, D_, F_ / 64, F_ * 2, 128, 64, 64, 4);
  enc(f, &p.mW1b, w1, 3, 64, D_, F_ / 64, F_ * 2, 128, 64, 64, 3);
  enc(f, &p.mW2, w2, 3, 64, F_, D_ / 64, D_ * 2, 128, 64, 64, 2);
  enc(f, &p.mO, po, 2, D_, S_, 1, D_ * 2, 0, 64, 64, 1);
  enc(f, &p.mH, ph, 2, D_, S_, 1, D_ * 2, 0, 64, 64, 1);
  enc(f, &p.mH1, ph1, 2, F_, S_, 1, F_ * 2, 0, 64, 64, 1);
  p.x = (const bf16*)x; p.w = (const bf16*)wqkv;
  cudaFuncSetAttribute(fused_block_kernel, cudaFuncAttributeMaxDynamicSharedMemorySize, SMEM_BYTES);
  cudaLaunchConfig_t cfg = {};
  cudaLaunchAttribute at;
  at.id = cudaLaunchAttributeClusterDimension; at.val.clusterDim.x = 2; at.val.clusterDim.y = 1; at.val.clusterDim.z = 1;
  cfg.gridDim = dim3(132); cfg.blockDim = dim3(384); cfg.dynamicSmemBytes = SMEM_BYTES; cfg.attrs = &at; cfg.numAttrs = 1;
  int ncl = 0;
  cudaOccupancyMaxActiveClusters(&ncl, fused_block_kernel, &cfg);
  if (ncl >= 66) {
    fused_block_kernel<<<132, 384, SMEM_BYTES>>>(p);
  } else {
    fused_block_kernel<<<4, 384, SMEM_BYTES>>>(p);
    fused_block_kernel<<<128, 384, SMEM_BYTES>>>(p);
  }
}
```

```cpp
#include <cuda_runtime.h>
#include <cuda_bf16.h>
#include <cuda.h>
#include <stdint.h>

namespace {

template <int FIRST> __device__ __forceinline__ void wgmma4_n128(float (&d)[64], uint32_t a, uint32_t b) {
#define WGD "{%0, %1, %2, %3, %4, %5, %6, %7, %8, %9, %10, %11, %12, %13, %14, %15, %16, %17, %18, %19, %20, %21, %22, %23, %24, %25, %26, %27, %28, %29, %30, %31, %32, %33, %34, %35, %36, %37, %38, %39, %40, %41, %42, %43, %44, %45, %46, %47, %48, %49, %50, %51, %52, %53, %54, %55, %56, %57, %58, %59, %60, %61, %62, %63}"
  asm volatile("{\n.reg .pred p, q;\n.reg .b64 da, db;\n.reg .b32 x, y;\nsetp.eq.b32 p, %66, 0;\nsetp.eq.b32 q, 0, 0;\n"
    "add.s32 x, %64, 0;\nadd.s32 y, %65, 0;\nmov.b64 da, {x, %67};\nmov.b64 db, {y, %67};\n"
    "wgmma.mma_async.sync.aligned.m64n128k16.f32.bf16.bf16 " WGD ", da, db, p, 1, 1, 0, 1;\n"
    "add.s32 x, %64, 2;\nadd.s32 y, %65, 128;\nmov.b64 da, {x, %67};\nmov.b64 db, {y, %67};\n"
    "wgmma.mma_async.sync.aligned.m64n128k16.f32.bf16.bf16 " WGD ", da, db, q, 1, 1, 0, 1;\n"
    "add.s32 x, %64, 4;\nadd.s32 y, %65, 256;\nmov.b64 da, {x, %67};\nmov.b64 db, {y, %67};\n"
    "wgmma.mma_async.sync.aligned.m64n128k16.f32.bf16.bf16 " WGD ", da, db, q, 1, 1, 0, 1;\n"
    "add.s32 x, %64, 6;\nadd.s32 y, %65, 384;\nmov.b64 da, {x, %67};\nmov.b64 db, {y, %67};\n"
    "wgmma.mma_async.sync.aligned.m64n128k16.f32.bf16.bf16 " WGD ", da, db, q, 1, 1, 0, 1;\n"
    "}\n"
    : "+f"(d[0]), "+f"(d[1]), "+f"(d[2]), "+f"(d[3]), "+f"(d[4]), "+f"(d[5]), "+f"(d[6]), "+f"(d[7]),
      "+f"(d[8]), "+f"(d[9]), "+f"(d[10]), "+f"(d[11]), "+f"(d[12]), "+f"(d[13]), "+f"(d[14]), "+f"(d[15]),
      "+f"(d[16]), "+f"(d[17]), "+f"(d[18]), "+f"(d[19]), "+f"(d[20]), "+f"(d[21]), "+f"(d[22]), "+f"(d[23]),
      "+f"(d[24]), "+f"(d[25]), "+f"(d[26]), "+f"(d[27]), "+f"(d[28]), "+f"(d[29]), "+f"(d[30]), "+f"(d[31]),
      "+f"(d[32]), "+f"(d[33]), "+f"(d[34]), "+f"(d[35]), "+f"(d[36]), "+f"(d[37]), "+f"(d[38]), "+f"(d[39]),
      "+f"(d[40]), "+f"(d[41]), "+f"(d[42]), "+f"(d[43]), "+f"(d[44]), "+f"(d[45]), "+f"(d[46]), "+f"(d[47]),
      "+f"(d[48]), "+f"(d[49]), "+f"(d[50]), "+f"(d[51]), "+f"(d[52]), "+f"(d[53]), "+f"(d[54]), "+f"(d[55]),
      "+f"(d[56]), "+f"(d[57]), "+f"(d[58]), "+f"(d[59]), "+f"(d[60]), "+f"(d[61]), "+f"(d[62]), "+f"(d[63])
    : "r"(a), "r"(b), "n"(FIRST), "r"(0x40000040));
#undef WGD
}

template <int FIRST> __device__ __forceinline__ void wgmma4_n192(float (&d)[96], uint32_t a, uint32_t b) {
#define WGD "{%0, %1, %2, %3, %4, %5, %6, %7, %8, %9, %10, %11, %12, %13, %14, %15, %16, %17, %18, %19, %20, %21, %22, %23, %24, %25, %26, %27, %28, %29, %30, %31, %32, %33, %34, %35, %36, %37, %38, %39, %40, %41, %42, %43, %44, %45, %46, %47, %48, %49, %50, %51, %52, %53, %54, %55, %56, %57, %58, %59, %60, %61, %62, %63, %64, %65, %66, %67, %68, %69, %70, %71, %72, %73, %74, %75, %76, %77, %78, %79, %80, %81, %82, %83, %84, %85, %86, %87, %88, %89, %90, %91, %92, %93, %94, %95}"
  asm volatile("{\n.reg .pred p, q;\n.reg .b64 da, db;\n.reg .b32 x, y;\nsetp.eq.b32 p, %98, 0;\nsetp.eq.b32 q, 0, 0;\n"
    "add.s32 x, %96, 0;\nadd.s32 y, %97, 0;\nmov.b64 da, {x, %99};\nmov.b64 db, {y, %99};\n"
    "wgmma.mma_async.sync.aligned.m64n192k16.f32.bf16.bf16 " WGD ", da, db, p, 1, 1, 0, 1;\n"
    "add.s32 x, %96, 2;\nadd.s32 y, %97, 128;\nmov.b64 da, {x, %99};\nmov.b64 db, {y, %99};\n"
    "wgmma.mma_async.sync.aligned.m64n192k16.f32.bf16.bf16 " WGD ", da, db, q, 1, 1, 0, 1;\n"
    "add.s32 x, %96, 4;\nadd.s32 y, %97, 256;\nmov.b64 da, {x, %99};\nmov.b64 db, {y, %99};\n"
    "wgmma.mma_async.sync.aligned.m64n192k16.f32.bf16.bf16 " WGD ", da, db, q, 1, 1, 0, 1;\n"
    "add.s32 x, %96, 6;\nadd.s32 y, %97, 384;\nmov.b64 da, {x, %99};\nmov.b64 db, {y, %99};\n"
    "wgmma.mma_async.sync.aligned.m64n192k16.f32.bf16.bf16 " WGD ", da, db, q, 1, 1, 0, 1;\n"
    "}\n"
    : "+f"(d[0]), "+f"(d[1]), "+f"(d[2]), "+f"(d[3]), "+f"(d[4]), "+f"(d[5]), "+f"(d[6]), "+f"(d[7]),
      "+f"(d[8]), "+f"(d[9]), "+f"(d[10]), "+f"(d[11]), "+f"(d[12]), "+f"(d[13]), "+f"(d[14]), "+f"(d[15]),
      "+f"(d[16]), "+f"(d[17]), "+f"(d[18]), "+f"(d[19]), "+f"(d[20]), "+f"(d[21]), "+f"(d[22]), "+f"(d[23]),
      "+f"(d[24]), "+f"(d[25]), "+f"(d[26]), "+f"(d[27]), "+f"(d[28]), "+f"(d[29]), "+f"(d[30]), "+f"(d[31]),
      "+f"(d[32]), "+f"(d[33]), "+f"(d[34]), "+f"(d[35]), "+f"(d[36]), "+f"(d[37]), "+f"(d[38]), "+f"(d[39]),
      "+f"(d[40]), "+f"(d[41]), "+f"(d[42]), "+f"(d[43]), "+f"(d[44]), "+f"(d[45]), "+f"(d[46]), "+f"(d[47]),
      "+f"(d[48]), "+f"(d[49]), "+f"(d[50]), "+f"(d[51]), "+f"(d[52]), "+f"(d[53]), "+f"(d[54]), "+f"(d[55]),
      "+f"(d[56]), "+f"(d[57]), "+f"(d[58]), "+f"(d[59]), "+f"(d[60]), "+f"(d[61]), "+f"(d[62]), "+f"(d[63]),
      "+f"(d[64]), "+f"(d[65]), "+f"(d[66]), "+f"(d[67]), "+f"(d[68]), "+f"(d[69]), "+f"(d[70]), "+f"(d[71]),
      "+f"(d[72]), "+f"(d[73]), "+f"(d[74]), "+f"(d[75]), "+f"(d[76]), "+f"(d[77]), "+f"(d[78]), "+f"(d[79]),
      "+f"(d[80]), "+f"(d[81]), "+f"(d[82]), "+f"(d[83]), "+f"(d[84]), "+f"(d[85]), "+f"(d[86]), "+f"(d[87]),
      "+f"(d[88]), "+f"(d[89]), "+f"(d[90]), "+f"(d[91]), "+f"(d[92]), "+f"(d[93]), "+f"(d[94]), "+f"(d[95])
    : "r"(a), "r"(b), "n"(FIRST), "r"(0x40000040));
#undef WGD
}

template <int FIRST> __device__ __forceinline__ void wgmma4_n256(float (&d)[128], uint32_t a, uint32_t b) {
#define WGD "{%0, %1, %2, %3, %4, %5, %6, %7, %8, %9, %10, %11, %12, %13, %14, %15, %16, %17, %18, %19, %20, %21, %22, %23, %24, %25, %26, %27, %28, %29, %30, %31, %32, %33, %34, %35, %36, %37, %38, %39, %40, %41, %42, %43, %44, %45, %46, %47, %48, %49, %50, %51, %52, %53, %54, %55, %56, %57, %58, %59, %60, %61, %62, %63, %64, %65, %66, %67, %68, %69, %70, %71, %72, %73, %74, %75, %76, %77, %78, %79, %80, %81, %82, %83, %84, %85, %86, %87, %88, %89, %90, %91, %92, %93, %94, %95, %96, %97, %98, %99, %100, %101, %102, %103, %104, %105, %106, %107, %108, %109, %110, %111, %112, %113, %114, %115, %116, %117, %118, %119, %120, %121, %122, %123, %124, %125, %126, %127}"
  asm volatile("{\n.reg .pred p, q;\n.reg .b64 da, db;\n.reg .b32 x, y;\nsetp.eq.b32 p, %130, 0;\nsetp.eq.b32 q, 0, 0;\n"
    "add.s32 x, %128, 0;\nadd.s32 y, %129, 0;\nmov.b64 da, {x, %131};\nmov.b64 db, {y, %131};\n"
    "wgmma.mma_async.sync.aligned.m64n256k16.f32.bf16.bf16 " WGD ", da, db, p, 1, 1, 0, 1;\n"
    "add.s32 x, %128, 2;\nadd.s32 y, %129, 128;\nmov.b64 da, {x, %131};\nmov.b64 db, {y, %131};\n"
    "wgmma.mma_async.sync.aligned.m64n256k16.f32.bf16.bf16 " WGD ", da, db, q, 1, 1, 0, 1;\n"
    "add.s32 x, %128, 4;\nadd.s32 y, %129, 256;\nmov.b64 da, {x, %131};\nmov.b64 db, {y, %131};\n"
    "wgmma.mma_async.sync.aligned.m64n256k16.f32.bf16.bf16 " WGD ", da, db, q, 1, 1, 0, 1;\n"
    "add.s32 x, %128, 6;\nadd.s32 y, %129, 384;\nmov.b64 da, {x, %131};\nmov.b64 db, {y, %131};\n"
    "wgmma.mma_async.sync.aligned.m64n256k16.f32.bf16.bf16 " WGD ", da, db, q, 1, 1, 0, 1;\n"
    "}\n"
    : "+f"(d[0]), "+f"(d[1]), "+f"(d[2]), "+f"(d[3]), "+f"(d[4]), "+f"(d[5]), "+f"(d[6]), "+f"(d[7]),
      "+f"(d[8]), "+f"(d[9]), "+f"(d[10]), "+f"(d[11]), "+f"(d[12]), "+f"(d[13]), "+f"(d[14]), "+f"(d[15]),
      "+f"(d[16]), "+f"(d[17]), "+f"(d[18]), "+f"(d[19]), "+f"(d[20]), "+f"(d[21]), "+f"(d[22]), "+f"(d[23]),
      "+f"(d[24]), "+f"(d[25]), "+f"(d[26]), "+f"(d[27]), "+f"(d[28]), "+f"(d[29]), "+f"(d[30]), "+f"(d[31]),
      "+f"(d[32]), "+f"(d[33]), "+f"(d[34]), "+f"(d[35]), "+f"(d[36]), "+f"(d[37]), "+f"(d[38]), "+f"(d[39]),
      "+f"(d[40]), "+f"(d[41]), "+f"(d[42]), "+f"(d[43]), "+f"(d[44]), "+f"(d[45]), "+f"(d[46]), "+f"(d[47]),
      "+f"(d[48]), "+f"(d[49]), "+f"(d[50]), "+f"(d[51]), "+f"(d[52]), "+f"(d[53]), "+f"(d[54]), "+f"(d[55]),
      "+f"(d[56]), "+f"(d[57]), "+f"(d[58]), "+f"(d[59]), "+f"(d[60]), "+f"(d[61]), "+f"(d[62]), "+f"(d[63]),
      "+f"(d[64]), "+f"(d[65]), "+f"(d[66]), "+f"(d[67]), "+f"(d[68]), "+f"(d[69]), "+f"(d[70]), "+f"(d[71]),
      "+f"(d[72]), "+f"(d[73]), "+f"(d[74]), "+f"(d[75]), "+f"(d[76]), "+f"(d[77]), "+f"(d[78]), "+f"(d[79]),
      "+f"(d[80]), "+f"(d[81]), "+f"(d[82]), "+f"(d[83]), "+f"(d[84]), "+f"(d[85]), "+f"(d[86]), "+f"(d[87]),
      "+f"(d[88]), "+f"(d[89]), "+f"(d[90]), "+f"(d[91]), "+f"(d[92]), "+f"(d[93]), "+f"(d[94]), "+f"(d[95]),
      "+f"(d[96]), "+f"(d[97]), "+f"(d[98]), "+f"(d[99]), "+f"(d[100]), "+f"(d[101]), "+f"(d[102]), "+f"(d[103]),
      "+f"(d[104]), "+f"(d[105]), "+f"(d[106]), "+f"(d[107]), "+f"(d[108]), "+f"(d[109]), "+f"(d[110]), "+f"(d[111]),
      "+f"(d[112]), "+f"(d[113]), "+f"(d[114]), "+f"(d[115]), "+f"(d[116]), "+f"(d[117]), "+f"(d[118]), "+f"(d[119]),
      "+f"(d[120]), "+f"(d[121]), "+f"(d[122]), "+f"(d[123]), "+f"(d[124]), "+f"(d[125]), "+f"(d[126]), "+f"(d[127])
    : "r"(a), "r"(b), "n"(FIRST), "r"(0x40000040));
#undef WGD
}

template <int FIRST> __device__ __forceinline__ void wgmma4(float (&d)[64], const uint32_t* a, uint32_t b) {
#define WGD "{%0, %1, %2, %3, %4, %5, %6, %7, %8, %9, %10, %11, %12, %13, %14, %15, %16, %17, %18, %19, %20, %21, %22, %23, %24, %25, %26, %27, %28, %29, %30, %31, %32, %33, %34, %35, %36, %37, %38, %39, %40, %41, %42, %43, %44, %45, %46, %47, %48, %49, %50, %51, %52, %53, %54, %55, %56, %57, %58, %59, %60, %61, %62, %63}"
  asm volatile("{\n.reg .pred p, q;\n.reg .b64 db;\n.reg .b32 y;\nsetp.eq.b32 p, %81, 0;\nsetp.eq.b32 q, 0, 0;\n"
    "add.s32 y, %80, 0;\nmov.b64 db, {y, %82};\n"
    "wgmma.mma_async.sync.aligned.m64n128k16.f32.bf16.bf16 " WGD ", {%64, %65, %66, %67}, db, p, 1, 1, 1;\n"
    "add.s32 y, %80, 128;\nmov.b64 db, {y, %82};\n"
    "wgmma.mma_async.sync.aligned.m64n128k16.f32.bf16.bf16 " WGD ", {%68, %69, %70, %71}, db, q, 1, 1, 1;\n"
    "add.s32 y, %80, 256;\nmov.b64 db, {y, %82};\n"
    "wgmma.mma_async.sync.aligned.m64n128k16.f32.bf16.bf16 " WGD ", {%72, %73, %74, %75}, db, q, 1, 1, 1;\n"
    "add.s32 y, %80, 384;\nmov.b64 db, {y, %82};\n"
    "wgmma.mma_async.sync.aligned.m64n128k16.f32.bf16.bf16 " WGD ", {%76, %77, %78, %79}, db, q, 1, 1, 1;\n"
    "}\n"
    : "+f"(d[0]), "+f"(d[1]), "+f"(d[2]), "+f"(d[3]), "+f"(d[4]), "+f"(d[5]), "+f"(d[6]), "+f"(d[7]),
      "+f"(d[8]), "+f"(d[9]), "+f"(d[10]), "+f"(d[11]), "+f"(d[12]), "+f"(d[13]), "+f"(d[14]), "+f"(d[15]),
      "+f"(d[16]), "+f"(d[17]), "+f"(d[18]), "+f"(d[19]), "+f"(d[20]), "+f"(d[21]), "+f"(d[22]), "+f"(d[23]),
      "+f"(d[24]), "+f"(d[25]), "+f"(d[26]), "+f"(d[27]), "+f"(d[28]), "+f"(d[29]), "+f"(d[30]), "+f"(d[31]),
      "+f"(d[32]), "+f"(d[33]), "+f"(d[34]), "+f"(d[35]), "+f"(d[36]), "+f"(d[37]), "+f"(d[38]), "+f"(d[39]),
      "+f"(d[40]), "+f"(d[41]), "+f"(d[42]), "+f"(d[43]), "+f"(d[44]), "+f"(d[45]), "+f"(d[46]), "+f"(d[47]),
      "+f"(d[48]), "+f"(d[49]), "+f"(d[50]), "+f"(d[51]), "+f"(d[52]), "+f"(d[53]), "+f"(d[54]), "+f"(d[55]),
      "+f"(d[56]), "+f"(d[57]), "+f"(d[58]), "+f"(d[59]), "+f"(d[60]), "+f"(d[61]), "+f"(d[62]), "+f"(d[63])
    : "r"(a[0]), "r"(a[1]), "r"(a[2]), "r"(a[3]), "r"(a[4]), "r"(a[5]), "r"(a[6]), "r"(a[7]), "r"(a[8]), "r"(a[9]), "r"(a[10]), "r"(a[11]), "r"(a[12]), "r"(a[13]), "r"(a[14]), "r"(a[15]),
      "r"(b), "n"(FIRST), "r"(0x40000040));
#undef WGD
}

template <int FIRST> __device__ __forceinline__ void wgmma4(float (&d)[128], const uint32_t* a, uint32_t b) {
#define WGD "{%0, %1, %2, %3, %4, %5, %6, %7, %8, %9, %10, %11, %12, %13, %14, %15, %16, %17, %18, %19, %20, %21, %22, %23, %24, %25, %26, %27, %28, %29, %30, %31, %32, %33, %34, %35, %36, %37, %38, %39, %40, %41, %42, %43, %44, %45, %46, %47, %48, %49, %50, %51, %52, %53, %54, %55, %56, %57, %58, %59, %60, %61, %62, %63, %64, %65, %66, %67, %68, %69, %70, %71, %72, %73, %74, %75, %76, %77, %78, %79, %80, %81, %82, %83, %84, %85, %86, %87, %88, %89, %90, %91, %92, %93, %94, %95, %96, %97, %98, %99, %100, %101, %102, %103, %104, %105, %106, %107, %108, %109, %110, %111, %112, %113, %114, %115, %116, %117, %118, %119, %120, %121, %122, %123, %124, %125, %126, %127}"
  asm volatile("{\n.reg .pred p, q;\n.reg .b64 db;\n.reg .b32 y;\nsetp.eq.b32 p, %145, 0;\nsetp.eq.b32 q, 0, 0;\n"
    "add.s32 y, %144, 0;\nmov.b64 db, {y, %146};\n"
    "wgmma.mma_async.sync.aligned.m64n256k16.f32.bf16.bf16 " WGD ", {%128, %129, %130, %131}, db, p, 1, 1, 1;\n"
    "add.s32 y, %144, 128;\nmov.b64 db, {y, %146};\n"
    "wgmma.mma_async.sync.aligned.m64n256k16.f32.bf16.bf16 " WGD ", {%132, %133, %134, %135}, db, q, 1, 1, 1;\n"
    "add.s32 y, %144, 256;\nmov.b64 db, {y, %146};\n"
    "wgmma.mma_async.sync.aligned.m64n256k16.f32.bf16.bf16 " WGD ", {%136, %137, %138, %139}, db, q, 1, 1, 1;\n"
    "add.s32 y, %144, 384;\nmov.b64 db, {y, %146};\n"
    "wgmma.mma_async.sync.aligned.m64n256k16.f32.bf16.bf16 " WGD ", {%140, %141, %142, %143}, db, q, 1, 1, 1;\n"
    "}\n"
    : "+f"(d[0]), "+f"(d[1]), "+f"(d[2]), "+f"(d[3]), "+f"(d[4]), "+f"(d[5]), "+f"(d[6]), "+f"(d[7]),
      "+f"(d[8]), "+f"(d[9]), "+f"(d[10]), "+f"(d[11]), "+f"(d[12]), "+f"(d[13]), "+f"(d[14]), "+f"(d[15]),
      "+f"(d[16]), "+f"(d[17]), "+f"(d[18]), "+f"(d[19]), "+f"(d[20]), "+f"(d[21]), "+f"(d[22]), "+f"(d[23]),
      "+f"(d[24]), "+f"(d[25]), "+f"(d[26]), "+f"(d[27]), "+f"(d[28]), "+f"(d[29]), "+f"(d[30]), "+f"(d[31]),
      "+f"(d[32]), "+f"(d[33]), "+f"(d[34]), "+f"(d[35]), "+f"(d[36]), "+f"(d[37]), "+f"(d[38]), "+f"(d[39]),
      "+f"(d[40]), "+f"(d[41]), "+f"(d[42]), "+f"(d[43]), "+f"(d[44]), "+f"(d[45]), "+f"(d[46]), "+f"(d[47]),
      "+f"(d[48]), "+f"(d[49]), "+f"(d[50]), "+f"(d[51]), "+f"(d[52]), "+f"(d[53]), "+f"(d[54]), "+f"(d[55]),
      "+f"(d[56]), "+f"(d[57]), "+f"(d[58]), "+f"(d[59]), "+f"(d[60]), "+f"(d[61]), "+f"(d[62]), "+f"(d[63]),
      "+f"(d[64]), "+f"(d[65]), "+f"(d[66]), "+f"(d[67]), "+f"(d[68]), "+f"(d[69]), "+f"(d[70]), "+f"(d[71]),
      "+f"(d[72]), "+f"(d[73]), "+f"(d[74]), "+f"(d[75]), "+f"(d[76]), "+f"(d[77]), "+f"(d[78]), "+f"(d[79]),
      "+f"(d[80]), "+f"(d[81]), "+f"(d[82]), "+f"(d[83]), "+f"(d[84]), "+f"(d[85]), "+f"(d[86]), "+f"(d[87]),
      "+f"(d[88]), "+f"(d[89]), "+f"(d[90]), "+f"(d[91]), "+f"(d[92]), "+f"(d[93]), "+f"(d[94]), "+f"(d[95]),
      "+f"(d[96]), "+f"(d[97]), "+f"(d[98]), "+f"(d[99]), "+f"(d[100]), "+f"(d[101]), "+f"(d[102]), "+f"(d[103]),
      "+f"(d[104]), "+f"(d[105]), "+f"(d[106]), "+f"(d[107]), "+f"(d[108]), "+f"(d[109]), "+f"(d[110]), "+f"(d[111]),
      "+f"(d[112]), "+f"(d[113]), "+f"(d[114]), "+f"(d[115]), "+f"(d[116]), "+f"(d[117]), "+f"(d[118]), "+f"(d[119]),
      "+f"(d[120]), "+f"(d[121]), "+f"(d[122]), "+f"(d[123]), "+f"(d[124]), "+f"(d[125]), "+f"(d[126]), "+f"(d[127])
    : "r"(a[0]), "r"(a[1]), "r"(a[2]), "r"(a[3]), "r"(a[4]), "r"(a[5]), "r"(a[6]), "r"(a[7]), "r"(a[8]), "r"(a[9]), "r"(a[10]), "r"(a[11]), "r"(a[12]), "r"(a[13]), "r"(a[14]), "r"(a[15]),
      "r"(b), "n"(FIRST), "r"(0x40000040));
#undef WGD
}

#define XSH 1
#define XS3 0
#define STAG 1
#define PREU 0
#define XRA 2
#define XR 37
#define NSL 100
#define NB0 1
#define NA0 1
#define GS 55
#define GH 23
#define G0 10
#define MPF 55
#define PACEH 1
#define PACE4 6
#define PACE3 2
#define PACE 2
#define ROT3 8
#define M5 15
#define SH4 1
#define SH3 1
#define SH0 1
#define PK0 3
#define AUX_GATE 3
#define XST 8
typedef __nv_bfloat16 bf16;
constexpr int S_ = 2048, D_ = 1024, F_ = 3584;
constexpr int OFF_SPARE = 160 * 1024, OFF_STG = 192 * 1024, OFF_CS = 224 * 1024, OFF_ST = OFF_CS + 1792, OFF_BAR = OFF_ST + 1024;
constexpr int SMEM_BYTES = 232448;
constexpr uint32_t SMEM_BASE = 1024;
enum { B_FULL = 0, B_EMPTY = 8, B_SFULL = 16, B_SFA = 18, B_HALO = 20, B_RDY0 = 22, B_RDY1 = 23, B_SEMPTY = 24, B_AUX = 26, B_NUM = 28, B_PEEK = 28 };
enum { F_O = 0, F_H = 64, F_H1 = 128, F_NUM = 192 };

struct Params {
  CUtensorMap mX, mWkv, mWq, mCq, mC1, mWo, mW1a, mW1b, mW2, mO, mH, mH1, mOut;
  const bf16* x;
};

__device__ __align__(1024) bf16 g_o[S_ * D_];
__device__ __align__(1024) bf16 g_h[S_ * D_];
__device__ __align__(1024) bf16 g_h1[S_ * F_];
__device__ __align__(128) float2 g_xst[2 * S_];
__device__ __align__(128) float2 g_hst[S_ * 8];
__device__ __align__(128) float g_cs[8 * 8 * 832];
__device__ __align__(128) uint4 g_halo[16 * 8 * 2 * 2 * 256];
__device__ __align__(128) uint32_t g_flag[F_NUM * 8];
__device__ uint32_t g_ctr;
#define PROF(idx) do {} while (0)

constexpr int SPIN_LIMIT = 1 << 22;

__device__ __forceinline__ void mbar_init(uint32_t bar, uint32_t cnt) { asm volatile("mbarrier.init.shared::cta.b64 [%0], %1;" ::"r"(bar), "r"(cnt)); }
__device__ __forceinline__ void mbar_expect_tx(uint32_t bar, uint32_t bytes) { asm volatile("mbarrier.arrive.expect_tx.shared::cta.b64 _, [%0], %1;" ::"r"(bar), "r"(bytes) : "memory"); }
__device__ __forceinline__ void mbar_arrive(uint32_t bar) { asm volatile("mbarrier.arrive.shared::cta.b64 _, [%0];" ::"r"(bar) : "memory"); }
__device__ __forceinline__ void mbar_arrive_cl(uint32_t bar_cluster_addr) { asm volatile("mbarrier.arrive.shared::cluster.b64 _, [%0];" ::"r"(bar_cluster_addr) : "memory"); }
__device__ __forceinline__ uint32_t mapa(uint32_t a, uint32_t cta) { uint32_t r; asm("mapa.shared::cluster.u32 %0, %1, %2;" : "=r"(r) : "r"(a), "r"(cta)); return r; }
__device__ __forceinline__ void spin_check(int& it) { asm volatile("{\n.reg .pred p;\nsetp.gt.s32 p, %0, %1;\n@p trap;\n}\n" ::"r"(++it), "n"(SPIN_LIMIT)); }
__device__ __forceinline__ void mbar_wait(uint32_t bar, uint32_t parity) {
  asm volatile("{\n.reg .pred p;\n.reg .s32 n;\nmov.s32 n, 0;\n"
               "W: mbarrier.try_wait.parity.shared::cta.b64 p, [%0], %1;\n@p bra D;\n"
               "add.s32 n, n, 1;\nsetp.lt.s32 p, n, %2;\n@p bra W;\ntrap;\nD:\n}\n" ::"r"(bar), "r"(parity), "n"(SPIN_LIMIT) : "memory");
}
__device__ __forceinline__ void mbar_wait_u(uint32_t bar, uint32_t parity, int& n) {
  asm volatile("{\n.reg .pred p;\n"
               "W: mbarrier.try_wait.parity.shared::cta.b64 p, [%1], %2;\n@!p add.s32 %0, %0, 1;\n"
               "setp.lt.and.s32 p, %0, %3, !p;\n@p bra.uni W;\n}\n" : "+r"(n) : "r"(bar), "r"(parity), "n"(SPIN_LIMIT) : "memory");
}
__device__ __forceinline__ void flag_add(int f) {
  asm volatile("red.relaxed.gpu.global.add.u32 [%0], 1;" ::"l"(g_flag + f * 8) : "memory");
}
__device__ __forceinline__ void flag_wait(int f, uint32_t target) {
  uint32_t v; int it = 0;
  do {
    asm volatile("ld.acquire.gpu.global.u32 %0, [%1];" : "=r"(v) : "l"(g_flag + f * 8) : "memory");
    spin_check(it);
  } while ((int)(v - target) < 0);
}
__device__ __forceinline__ void flag_peek(uint32_t dst, int f) {
  asm volatile("cp.async.cg.shared.global [%0], [%1], 16;\ncp.async.commit_group;" ::"r"(dst), "l"(g_flag + f * 8) : "memory");
}
__device__ __forceinline__ bool flag_seen(uint32_t src, uint32_t ep1) {
  uint32_t v;
  asm volatile("cp.async.wait_group 0;\nld.shared.u32 %0, [%1];" : "=r"(v) : "r"(src) : "memory");
  return (int)(v - 8 * ep1) >= 0;
}
__device__ __forceinline__ void fence_async_global() { asm volatile("fence.proxy.async.global;" ::: "memory"); }
__device__ __forceinline__ void fence_async_smem() { asm volatile("fence.proxy.async.shared::cta;" ::: "memory"); }
__device__ __forceinline__ void tma2d(uint32_t dst, const CUtensorMap* m, uint32_t bar, int c0, int c1) {
  asm volatile("cp.async.bulk.tensor.2d.shared::cluster.global.mbarrier::complete_tx::bytes [%0], [%1, {%3, %4}], [%2];"
               ::"r"(dst), "l"(m), "r"(bar), "r"(c0), "r"(c1) : "memory");
}
__device__ __forceinline__ void bulk_s2s(uint32_t dst_cl, uint32_t src, uint32_t bytes, uint32_t bar_cl) {
  asm volatile("cp.async.bulk.shared::cluster.shared::cta.mbarrier::complete_tx::bytes [%0], [%1], %2, [%3];" ::"r"(dst_cl), "r"(src), "r"(bytes), "r"(bar_cl) : "memory");
}
__device__ __forceinline__ void map_prefetch(const CUtensorMap* m) { asm volatile("prefetch.tensormap [%0];" ::"l"(m) : "memory"); }
__device__ __forceinline__ void tma2d_mc(uint32_t dst, const CUtensorMap* m, uint32_t bar, int c0, int c1, uint16_t mask = 3) {
  asm volatile("cp.async.bulk.tensor.2d.shared::cluster.global.mbarrier::complete_tx::bytes.multicast::cluster [%0], [%1, {%3, %4}], [%2], %5;"
               ::"r"(dst), "l"(m), "r"(bar), "r"(c0), "r"(c1), "h"(mask) : "memory");
}
__device__ __forceinline__ void tma3d(uint32_t dst, const CUtensorMap* m, uint32_t bar, int c0, int c1, int c2) {
  asm volatile("cp.async.bulk.tensor.3d.shared::cluster.global.mbarrier::complete_tx::bytes [%0], [%1, {%3, %4, %5}], [%2];"
               ::"r"(dst), "l"(m), "r"(bar), "r"(c0), "r"(c1), "r"(c2) : "memory");
}
__device__ __forceinline__ void tma4d(uint32_t dst, const CUtensorMap* m, uint32_t bar, int c0, int c1, int c2, int c3) {
  asm volatile("cp.async.bulk.tensor.4d.shared::cluster.global.mbarrier::complete_tx::bytes [%0], [%1, {%3, %4, %5, %6}], [%2];"
               ::"r"(dst), "l"(m), "r"(bar), "r"(c0), "r"(c1), "r"(c2), "r"(c3) : "memory");
}
__device__ __forceinline__ void tma3d_mc(uint32_t dst, const CUtensorMap* m, uint32_t bar, int c0, int c1, int c2) {
  asm volatile("cp.async.bulk.tensor.3d.shared::cluster.global.mbarrier::complete_tx::bytes.multicast::cluster [%0], [%1, {%3, %4, %5}], [%2], %6;"
               ::"r"(dst), "l"(m), "r"(bar), "r"(c0), "r"(c1), "r"(c2), "h"((uint16_t)3) : "memory");
}
__device__ __forceinline__ void tma2d_st(const CUtensorMap* m, uint32_t src, int c0, int c1) {
  asm volatile("cp.async.bulk.tensor.2d.global.shared::cta.bulk_group [%0, {%2, %3}], [%1];" ::"l"(m), "r"(src), "r"(c0), "r"(c1) : "memory");
}
__device__ __forceinline__ void tma3d_st(const CUtensorMap* m, uint32_t src, int c0, int c1, int c2) {
  asm volatile("cp.async.bulk.tensor.3d.global.shared::cta.bulk_group [%0, {%2, %3, %4}], [%1];" ::"l"(m), "r"(src), "r"(c0), "r"(c1), "r"(c2) : "memory");
}
__device__ __forceinline__ void bulk_commit() { asm volatile("cp.async.bulk.commit_group;" ::: "memory"); }
__device__ __forceinline__ void bulk_wait_read() { asm volatile("cp.async.bulk.wait_group.read 0;" ::: "memory"); }
__device__ __forceinline__ void bulk_wait_all() { asm volatile("cp.async.bulk.wait_group 0;" ::: "memory"); }
__device__ __forceinline__ void wg_fence() { asm volatile("wgmma.fence.sync.aligned;" ::: "memory"); }
__device__ __forceinline__ void wg_commit() { asm volatile("wgmma.commit_group.sync.aligned;" ::: "memory"); }
template <int N> __device__ __forceinline__ void wg_wait() { asm volatile("wgmma.wait_group.sync.aligned %0;" ::"n"(N) : "memory"); }
template <int N> __device__ __forceinline__ void reg_fence(float (&a)[N]) {
#pragma unroll
  for (int i = 0; i < N; i++) asm volatile("" : "+f"(a[i])::"memory");
}
__device__ __forceinline__ void named_sync(int id, int n) { asm volatile("bar.sync %0, %1;" ::"r"(id), "r"(n) : "memory"); }
__device__ __forceinline__ uint32_t pack2(float lo, float hi) { uint32_t r; asm("cvt.rn.bf16x2.f32 %0, %1, %2;" : "=r"(r) : "f"(hi), "f"(lo)); return r; }
__device__ __forceinline__ uint32_t pack2_relu(float lo, float hi) { uint32_t r; asm("cvt.rn.relu.bf16x2.f32 %0, %1, %2;" : "=r"(r) : "f"(hi), "f"(lo)); return r; }
__device__ __forceinline__ float ex2(float x) { float r; asm("ex2.approx.ftz.f32 %0, %1;" : "=f"(r) : "f"(x)); return r; }
__device__ __forceinline__ float rcp(float x) { float r; asm("rcp.approx.ftz.f32 %0, %1;" : "=f"(r) : "f"(x)); return r; }
__device__ __forceinline__ float bf_lo(uint32_t v) { return __uint_as_float(v << 16); }
__device__ __forceinline__ float bf_hi(uint32_t v) { return __uint_as_float(v & 0xFFFF0000u); }
__device__ __forceinline__ uint4 ldcg128(const void* p) { uint4 v; asm volatile("ld.global.cg.v4.b32 {%0, %1, %2, %3}, [%4];" : "=r"(v.x), "=r"(v.y), "=r"(v.z), "=r"(v.w) : "l"(p)); return v; }
__device__ __forceinline__ void stsm4(uint32_t a, uint32_t r0, uint32_t r1, uint32_t r2, uint32_t r3) {
  asm volatile("stmatrix.sync.aligned.m8n8.x4.shared.b16 [%0], {%1, %2, %3, %4};" ::"r"(a), "r"(r0), "r"(r1), "r"(r2), "r"(r3) : "memory");
}
__device__ __forceinline__ void ldsm4(uint32_t a, uint32_t& r0, uint32_t& r1, uint32_t& r2, uint32_t& r3) {
  asm volatile("ldmatrix.sync.aligned.m8n8.x4.shared.b16 {%0, %1, %2, %3}, [%4];" : "=r"(r0), "=r"(r1), "=r"(r2), "=r"(r3) : "r"(a) : "memory");
}
__device__ __forceinline__ uint32_t movm(uint32_t a) { uint32_t d; asm volatile("movmatrix.sync.aligned.m8n8.trans.b16 %0, %1;" : "=r"(d) : "r"(a)); return d; }
__device__ __forceinline__ void mma16(float (&c)[4], uint32_t a0, uint32_t a1, uint32_t a2, uint32_t a3, uint32_t b0, uint32_t b1) {
  asm volatile("mma.sync.aligned.m16n8k16.row.col.f32.bf16.bf16.f32 {%0,%1,%2,%3}, {%4,%5,%6,%7}, {%8,%9}, {%0,%1,%2,%3};"
               : "+f"(c[0]), "+f"(c[1]), "+f"(c[2]), "+f"(c[3]) : "r"(a0), "r"(a1), "r"(a2), "r"(a3), "r"(b0), "r"(b1));
}
__device__ __forceinline__ void mma8(float (&c)[4], uint32_t a0, uint32_t a1, uint32_t b0) {
  asm volatile("mma.sync.aligned.m16n8k8.row.col.f32.bf16.bf16.f32 {%0,%1,%2,%3}, {%4,%5}, {%6}, {%0,%1,%2,%3};"
               : "+f"(c[0]), "+f"(c[1]), "+f"(c[2]), "+f"(c[3]) : "r"(a0), "r"(a1), "r"(b0));
}
__device__ __forceinline__ float2 lds64f(uint32_t a) { float2 v; asm volatile("ld.shared.v2.f32 {%0, %1}, [%2];" : "=f"(v.x), "=f"(v.y) : "r"(a)); return v; }
__device__ __forceinline__ uint4 lds128(uint32_t a) { uint4 v; asm volatile("ld.shared.v4.b32 {%0, %1, %2, %3}, [%4];" : "=r"(v.x), "=r"(v.y), "=r"(v.z), "=r"(v.w) : "r"(a)); return v; }
__device__ __forceinline__ void sts128(uint32_t a, uint32_t x, uint32_t y, uint32_t z, uint32_t w) { asm volatile("st.shared.v4.b32 [%0], {%1, %2, %3, %4};" ::"r"(a), "r"(x), "r"(y), "r"(z), "r"(w) : "memory"); }
__device__ __forceinline__ void sts64f(uint32_t a, float x, float y) { asm volatile("st.shared.v2.f32 [%0], {%1, %2};" ::"r"(a), "f"(x), "f"(y) : "memory"); }
__device__ __forceinline__ float4 lds128f(uint32_t a) { float4 v; asm volatile("ld.shared.v4.f32 {%0, %1, %2, %3}, [%4];" : "=f"(v.x), "=f"(v.y), "=f"(v.z), "=f"(v.w) : "r"(a)); return v; }
__device__ __forceinline__ void st_tag2(void* p, float x, float y, uint32_t tag) {
  asm volatile("st.relaxed.gpu.global.v2.b32 [%0], {%1, %2};" ::"l"(p), "r"((__float_as_uint(x) & ~3u) | tag), "r"((__float_as_uint(y) & ~3u) | tag) : "memory");
}
__device__ __forceinline__ float4 ld_tag4(const void* p) { float4 v; asm volatile("ld.relaxed.gpu.global.v4.f32 {%0, %1, %2, %3}, [%4];" : "=f"(v.x), "=f"(v.y), "=f"(v.z), "=f"(v.w) : "l"(p) : "memory"); return v; }
__device__ __forceinline__ uint32_t tag_bad(const float4& v, uint32_t tag) {
  return ((__float_as_uint(v.x) ^ tag) | (__float_as_uint(v.y) ^ tag) | (__float_as_uint(v.z) ^ tag) | (__float_as_uint(v.w) ^ tag)) & 3u;
}

template <int F> __device__ __forceinline__ void wgmma4(float (&d)[64], uint32_t a, uint32_t b) { wgmma4_n128<F>(d, a, b); }
template <int F> __device__ __forceinline__ void wgmma4(float (&d)[96], uint32_t a, uint32_t b) { wgmma4_n192<F>(d, a, b); }
template <int F> __device__ __forceinline__ void wgmma4(float (&d)[128], uint32_t a, uint32_t b) { wgmma4_n256<F>(d, a, b); }

struct Ctx { uint32_t sb, bar, ep1; int i, j, rank; };
template <int PH> struct Geo {
  static constexpr int N0 = PH * 16;
  static constexpr int NS = PH == 5 ? 56 : 16;
  static constexpr int NCH = (PH == 0 || PH == 3) ? 4 : (PH == 4 ? 3 : 2);
  static constexpr int SB = 16384 + NCH * 8192;
  static constexpr int DEPTH = NCH == 2 ? 6 : 4;
  static constexpr int SLOT0 = PH == 0 ? 1 : PH == 1 ? 2 : PH == 3 ? 3 : 0;
  static __device__ __forceinline__ int dep(int m) {
    if (PH == 5 && m >= 5 && m <= M5) return m < M5 ? N0 + m - 5 : -1;
    if (m >= DEPTH || PH == 0 || PH == 2) return N0 + m - DEPTH;
    if (PH == 1) return m == 0 ? 12 : 13 + (m >> 1);
    if (PH == 3) return m == 0 ? N0 - 5 : N0 - 4 + m;
    if (PH == 4) return N0 - 3 + (m < 2 ? m : 2);
    return N0 - 4 + (m < 3 ? m : 3);
  }
  static __device__ __forceinline__ int next(int slot, int m) { return slot + 1 == (PH == 5 && m < M5 - 5 ? 5 : DEPTH) ? 0 : slot + 1; }
  static __device__ __forceinline__ int slot_of(int m) { return PH == 5 ? (m >= M5 - 5 ? (m - M5 + 5) % 6 : m % 5) : (SLOT0 + m) % DEPTH; }
  static __device__ __forceinline__ bool own(int m) { return (PH == 2 || PH == 3) && m < 2; }
  static __device__ __forceinline__ bool local(int m) { return (PH == 2 || PH == 3) && m < 4; }
  static __device__ __forceinline__ int koff(int m, int j) {
    if (local(m)) return (128 * j) ^ (64 * m);
    if (PH == 2 || PH == 3) { const int t = m < 10 ? m - 4 : m - 10; return 128 * (t < (j & 6) ? t : t + 2) + (m < 10 ? 0 : 64); }
    if (PH == 5) return m < 32 ? 448 * (m >> 2) + 64 * (m & 3) : 448 * ((m - 32) / 3) + 256 + 64 * ((m - 32) % 3);
    return 64 * m;
  }
};
__device__ __forceinline__ void wait_empty(const Ctx& c, int d) { mbar_wait(c.bar + 8 * (B_EMPTY + (d & 7)), (d >> 3) & 1); }

__device__ __forceinline__ void set_progress(const Ctx& c, int d) { asm volatile("st.volatile.shared.s32 [%0], %1;" ::"r"(c.bar + 8 * B_PEEK + 16), "r"(d) : "memory"); }
__device__ __forceinline__ void wait_progress(const Ctx& c, int d) {
  asm volatile("{\n.reg .pred p;\n.reg .s32 n, v;\nmov.s32 n, 0;\n"
               "W: ld.volatile.shared.s32 v, [%0];\nsetp.ge.s32 p, v, %1;\n@p bra D;\nnanosleep.u32 %3;\n"
               "add.s32 n, n, 1;\nsetp.lt.s32 p, n, %2;\n@p bra W;\ntrap;\nD:\n}\n" ::"r"(c.bar + 8 * B_PEEK + 16), "r"(d), "n"(SPIN_LIMIT), "n"(NSL) : "memory");
}
static_assert(PACE4 + PACE <= M5 - 6, "the first h1 stores must not wait for slot 5");

template <int PH> __device__ __forceinline__ void produce_b(const Params& p, const Ctx& c, int m0, int m1) {
  using G = Geo<PH>;
  int slot = G::slot_of(m0);
#pragma unroll 1
  for (int m = m0; m < m1; m++) {
    const int n = G::N0 + m, d = G::dep(m);
    if (d >= 0) wait_empty(c, d);
    if (PH == 5 && m == M5) { mbar_wait(c.bar + 8 * B_SEMPTY, 1); mbar_wait(c.bar + 8 * (B_SEMPTY + 1), 1); }
    const uint32_t fb = c.bar + 8 * (n & 7), dst = c.sb + slot * G::SB + 16384;
    mbar_expect_tx(fb, G::own(m) ? G::SB - 16384 : G::SB);
    const int k0 = G::koff(m, c.j);
    if (PH == 0 && m < NA0) { tma3d(dst - 16384, &p.mX, fb, k0, 0, 64 * c.i); tma3d(dst - 8192, &p.mX, fb, k0, 1, 64 * c.i); }
    if (PH == 0) tma4d(dst, &p.mWkv, fb, 0, k0, 2 * c.j, 1);
    if (PH == 1) tma3d(dst, &p.mWq, fb, 0, k0, 2 * c.j);
    if (PH == 2) tma3d(dst, &p.mWo, fb, 0, k0, 2 * c.j);
    if (PH == 3) tma3d(dst, &p.mW1a, fb, 0, k0, 7 * c.j);
    if (PH == 4) tma3d(dst, &p.mW1b, fb, 0, k0, 7 * c.j + 4);
    if (PH == 5) tma3d(dst, &p.mW2, fb, 0, k0, 2 * c.j);
    if (d >= 0) set_progress(c, d);
    if (PH == 0 && m == 0) PROF(2);
    if (PH == 5 && m == MPF) map_prefetch(&p.mOut);
    slot = G::next(slot, m);
  }
}
template <int PH> __device__ __forceinline__ void produce_a(const Params& p, const Ctx& c, bool& seen) {
  using G = Geo<PH>;
  constexpr int M1 = PH == 5 ? 32 : PH == 4 ? 16 : 10;
  const int F0 = (PH == 2 ? F_O : PH == 3 ? F_H : F_H1) + c.i * 4 + c.rank;
  int slot = G::SLOT0;
  const int row = 128 * c.i + 64 * c.rank;
#pragma unroll 1
  for (int m = 0; m < G::NS; m++) {
    if (!G::local(m) && (PH > 0 || m >= NA0)) {
      const int n = G::N0 + m, d = G::dep(m);
      if (m == 4 && (PH == 2 || PH == 3)) { flag_wait(F0, 8 * c.ep1); fence_async_global(); PROF(PH == 2 ? 24 : 26); }
      if (d >= 0) wait_empty(c, d);
      if ((m == M1 && PH >= 2 && PH != 4) || (PH == 5 && m == 0)) {
        if (!seen) { if (!flag_seen(c.bar + 8 * B_PEEK, c.ep1)) flag_wait(F0 + (m ? 2 : 0), 8 * c.ep1); fence_async_global(); }
        PROF(PH == 2 ? 25 : PH == 3 ? 29 : 27 + (m >> 5));
      }
      const uint32_t fb = c.bar + 8 * (n & 7), dst = c.sb + slot * G::SB + c.rank * 8192;
      const int k0 = G::koff(m, c.j);
      if (PH <= 1) tma3d_mc(dst, &p.mX, fb, k0, c.rank, 64 * c.i);
      if (PH == 2) tma2d_mc(dst, &p.mO, fb, k0, row);
      if (PH == 3 || PH == 4) tma2d_mc(dst, &p.mH, fb, k0, row);
      if (PH == 5) tma2d_mc(dst, &p.mH1, fb, k0, row);
      if (PH == 0 && m == NA0) PROF(3);
      if (PH >= 2 && (m == M1 - PK0 || m == M1 - 1)) {
        seen = m == M1 - 1 && flag_seen(c.bar + 8 * B_PEEK, c.ep1);
        if (seen) fence_async_global(); else flag_peek(c.bar + 8 * B_PEEK, F0 + (PH == 4 ? 0 : 2));
      }
    }
    slot = G::next(slot, m);
  }
}

struct Con { uint32_t rel, stg, da; int wg, w, lane, spin; bool do_rel; };
template <int PH, bool FIRST, bool RS = false> __device__ __forceinline__ void issue(float (&acc)[Geo<PH>::NCH * 32], const Ctx& c, Con& k, int m, int slot, const uint32_t* ar = nullptr) {
  using G = Geo<PH>;
  const int n = G::N0 + m;
  mbar_wait_u(c.bar + 8 * (n & 7), (n >> 3) & 1, k.spin);
  if (m == 0 && k.do_rel) PROF(32 + 32 * k.wg + 3 * PH);
  if (PH == 2 && (m == 4 || m == 10) && k.do_rel) PROF(32 + 32 * k.wg + 19 + (m >> 3));
  if (PH == 3 && (m == 2 || m == 4) && k.do_rel) PROF(32 + 32 * k.wg + 20 + (m >> 1));
  if (PH == 2 && (m == 2 || m == 3 || m == 5) && k.do_rel) PROF(32 + 32 * k.wg + 22 + m);
  if (PH == 3 && (m == 3 || m == 10) && k.do_rel) PROF(32 + 32 * k.wg + 28 + (m >> 3));
  const uint32_t so = slot * (G::SB >> 4);
  wg_fence();
  if constexpr (RS) wgmma4<FIRST>(acc, ar, so + (((SMEM_BASE + 16384) >> 4) | (512u << 16)));
  else wgmma4<FIRST>(acc, k.da + so, so + (((SMEM_BASE + 16384) >> 4) | (512u << 16)));
  wg_commit();
}
template <int PH> __device__ __forceinline__ void retire(Con& k, int m) {
  wg_wait<1>();
  if (k.do_rel && (PH < 5 || m <= 50)) mbar_arrive_cl(k.rel + 8 * ((Geo<PH>::N0 + m - 1) & 7));
}
template <int PH, int PEND = 0> __device__ __forceinline__ void finish(Con& k) {
  wg_wait<PEND>();
  if (PH < 5 && k.do_rel) mbar_arrive_cl(k.rel + 8 * 7);
  if (k.do_rel) PROF(32 + 32 * k.wg + 3 * PH + 1);
}
template <int PH> __device__ __forceinline__ void steps(float (&acc)[Geo<PH>::NCH * 32], const Ctx& c, Con& k, int m0, int m1) {
  using G = Geo<PH>;
  int slot = G::slot_of(m0);
#pragma unroll 1
  for (int m = m0; m < m1; m++) {
    issue<PH, false>(acc, c, k, m, slot);
    retire<PH>(k, m);
    slot = G::next(slot, m);
  }
}
#define ISSUE(PH, acc, m) issue<PH, false>(acc, c, k, m, Geo<PH>::slot_of(m))
#define ISSUE_RS(PH, acc, r) issue<PH, true, true>(acc, c, k, 0, Geo<PH>::SLOT0, r); issue<PH, false, true>(acc, c, k, 1, Geo<PH>::slot_of(1), r + 16); retire<PH>(k, 1)
#define LAST(PH, acc, on) \
  if (on && k.wg) { pre_load<PH>(pr, c, k); wg_wait<0>(); if (k.do_rel) mbar_arrive_cl(k.rel + 8 * 6); named_sync(4, 256); } \
  ISSUE(PH, acc, 15); \
  if (!(on && k.wg)) { pre_load<PH>(pr, c, k); retire<PH>(k, 15); } \
  finish<PH>(k); \
  if (on && !k.wg) asm volatile("bar.arrive 4, 256;" ::: "memory")
#define ISSUE0(PH, acc) issue<PH, true>(acc, c, k, 0, Geo<PH>::SLOT0)

__device__ __forceinline__ void handoff(const Ctx& c, Con& k, int bar = B_SFULL) {
  fence_async_smem();
  __syncwarp();
  if (k.lane == 0) mbar_arrive(c.bar + 8 * (bar + k.wg));
}

struct Pre { float4 cs[4]; float2 s0, s1; };
template <int PH> __device__ __forceinline__ void pre_load(Pre& a, const Ctx& c, Con& k) {
  if (PH == 0) mbar_wait_u(c.bar + 8 * B_RDY0, 0, k.spin);
  if (PH == 1) { mbar_wait_u(c.bar + 8 * B_RDY1, 0, k.spin); mbar_wait_u(c.bar + 8 * (B_HALO + k.wg), 0, k.spin); }
  if (PH == 4) { mbar_wait_u(c.bar + 8 * B_RDY1, 1, k.spin); mbar_wait_u(c.bar + 8 * (B_SEMPTY + k.wg), 0, k.spin); }
  if (PH == 3) { mbar_wait_u(c.bar + 8 * B_RDY0, 1, k.spin); mbar_wait_u(c.bar + 8 * (B_EMPTY + 4), 1, k.spin); }
  const uint32_t sta = c.sb + OFF_ST + (k.wg * 64 + k.w * 16 + (k.lane >> 2)) * 8;
  a.s0 = lds64f(sta); a.s1 = lds64f(sta + 64);
  a.s0.x = -a.s0.x; a.s1.x = -a.s1.x;
#pragma unroll
  for (int u = 0; u < 4; u++) a.cs[u] = lds128f(c.sb + OFF_CS + (Geo<PH>::NCH == 4 ? 0 : 1024) + (PH == 3 ? u ^ ROT3 : u) * 64 + (k.lane & 3) * 16);
}
template <int PH, int U0, int U1> __device__ __forceinline__ void qkv_pack(uint32_t (&pk)[Geo<PH>::NCH * 8][2], const float (&acc)[Geo<PH>::NCH * 32], Pre& a, const Ctx& c, Con& k) {
  const uint32_t csa = c.sb + OFF_CS + PH * 1024 + (k.lane & 3) * 16;
#pragma unroll
  for (int u = U0; u < U1; u++) {
    const float4 s = a.cs[u & 3];
    if (u + 4 < Geo<PH>::NCH * 4) a.cs[u & 3] = lds128f(csa + (u + 4) * 64);
    float v[8];
#pragma unroll
    for (int e = 0; e < 8; e++) {
      v[e] = fmaf((e & 2) ? a.s1.x : a.s0.x, (e & 4) ? ((e & 1) ? s.w : s.z) : ((e & 1) ? s.y : s.x), acc[8 * u + e]);
      if (PH == 0) v[e] *= (e & 2) ? a.s1.y : a.s0.y;
    }
#pragma unroll
    for (int e = 0; e < 4; e++) pk[2 * u + (e >> 1)][e & 1] = pack2(v[2 * e], v[2 * e + 1]);
  }
}
#define HALO_SRC(kv, H, x) kv[((x) < 8 ? 0 : 8) + 8 * (H) + (x)][1]
template <int H> __device__ __forceinline__ void halo_publish(uint32_t (&kv)[32][2], const Ctx& c, Con& k) {
  if (k.w < 3) {
    const uint32_t ha = k.stg + (k.w + 1) * 2048 + k.lane * 16;
#pragma unroll
    for (int u = 4 * H; u < 4 * H + 4; u++)
      sts128(ha + (u >> 2) * 8192 + (u & 3) * 512, HALO_SRC(kv, u >> 2, 4 * (u & 3)), HALO_SRC(kv, u >> 2, 4 * (u & 3) + 1), HALO_SRC(kv, u >> 2, 4 * (u & 3) + 2), HALO_SRC(kv, u >> 2, 4 * (u & 3) + 3));
    __syncwarp();
    if (H == 1 && k.lane == 0) mbar_arrive(c.bar + 8 * (B_HALO + k.wg));
  } else if (c.i < 15) {
    uint4* hp = g_halo + ((c.i * 8 + c.j) * 2 + k.wg) * 512 + k.lane;
#pragma unroll
    for (int u = 8 * H; u < 8 * H + 8; u++) {
      const unsigned long long x = ((unsigned long long)c.ep1 << 32) | HALO_SRC(kv, u >> 3, 2 * (u & 7)), y = ((unsigned long long)c.ep1 << 32) | HALO_SRC(kv, u >> 3, 2 * (u & 7) + 1);
      asm volatile("st.relaxed.gpu.global.v2.b64 [%0], {%1, %2};" ::"l"(hp + u * 32), "l"(x), "l"(y) : "memory");
    }
  }
}
struct Att { uint32_t hl[16], pp[4][2], z[4]; float l[4][2], mx[4], o[8][4], dn[2][4]; };
template <int H> __device__ __forceinline__ void att_halo(Att& s, Con& k) {
#pragma unroll
  for (int u = 0; u < 4; u++) { const uint4 v = lds128(k.stg + H * 8192 + k.w * 2048 + k.lane * 16 + u * 512); s.hl[4 * u] = v.x; s.hl[4 * u + 1] = v.y; s.hl[4 * u + 2] = v.z; s.hl[4 * u + 3] = v.w; }
}
template <int H> __device__ __forceinline__ void att_qk(Att& s, const uint32_t (&q)[16][2], uint32_t (&kv)[32][2], float lmask, const Ctx& c, Con& k) {
  auto& hl = s.hl; auto& l = s.l;
  const bool g0 = 2 * (k.lane & 3) > (k.lane >> 2), g1 = 2 * (k.lane & 3) + 1 > (k.lane >> 2), nohalo = (k.w == 0 && c.i == 0);
  float sa[2][4], sb[2][4], sh[2][4];
#pragma unroll
  for (int e = 0; e < 8; e++) { sa[e >> 2][e & 3] = 0.f; sb[e >> 2][e & 3] = 0.f; sh[e >> 2][e & 3] = 0.f; }
#pragma unroll
  for (int ks = 0; ks < 2; ks++)
#pragma unroll
    for (int hd = 0; hd < 2; hd++) {
      const int x = 4 * hd + 2 * ks, t = 8 * H + x;
      mma16(sa[hd], q[t][0], q[t][1], q[t + 1][0], q[t + 1][1], kv[t][0], kv[t + 1][0]);
      mma16(sb[hd], q[t][0], q[t][1], q[t + 1][0], q[t + 1][1], kv[t][1], kv[t + 1][1]);
      mma16(sh[hd], q[t][0], q[t][1], q[t + 1][0], q[t + 1][1], hl[x], hl[x + 1]);
    }
#pragma unroll
  for (int t = 16 + 8 * H; t < 24 + 8 * H; t++) kv[t][0] = movm(kv[t][0]);
#pragma unroll
  for (int hd = 0; hd < 2; hd++) {
    if (nohalo) sh[hd][0] = sh[hd][1] = lmask;
    l[2 * hd][0] = g0 ? sh[hd][0] : sa[hd][0]; l[2 * hd][1] = g1 ? sh[hd][1] : sa[hd][1];
    l[2 * hd + 1][0] = g0 ? sa[hd][2] : sb[hd][2]; l[2 * hd + 1][1] = g1 ? sa[hd][3] : sb[hd][3];
  }
}
__device__ __forceinline__ void att_soft(Att& s, float sc0, float sc1, Con& k) {
  auto& l = s.l; auto& mx = s.mx; auto& pp = s.pp; auto& z = s.z;
  const bool g0 = 2 * (k.lane & 3) > (k.lane >> 2), g1 = 2 * (k.lane & 3) + 1 > (k.lane >> 2);
#pragma unroll
  for (int e = 0; e < 4; e++) mx[e] = fmaxf(l[e][0], l[e][1]);
#pragma unroll
  for (int o = 1; o < 3; o++)
#pragma unroll
    for (int e = 0; e < 4; e++) mx[e] = fmaxf(mx[e], __shfl_xor_sync(~0u, mx[e], o));
#pragma unroll
  for (int e = 0; e < 4; e++) {
    const float sc = (e & 1) ? sc1 : sc0;
    const uint32_t pr = pack2(ex2((l[e][0] - mx[e]) * sc), ex2((l[e][1] - mx[e]) * sc)), mk = (g0 ? 0xFFFFu : 0u) | (g1 ? 0xFFFF0000u : 0u);
    pp[e][0] = pr & mk; pp[e][1] = pr & ~mk; z[e] = pr & (k.spin >> 31);
    mx[e] = __uint_as_float(pr);
  }
}
template <int H> __device__ __forceinline__ void att_pv(Att& s, const uint32_t (&kv)[32][2]) {
  auto& hl = s.hl; auto& mx = s.mx; auto& pp = s.pp; auto& z = s.z; auto& o = s.o; auto& dn = s.dn;
#pragma unroll
  for (int hd = 0; hd < 2; hd++) {
    dn[hd][0] = dn[hd][1] = dn[hd][2] = dn[hd][3] = 0.f;
    mma8(dn[hd], __float_as_uint(mx[2 * hd]), __float_as_uint(mx[2 * hd + 1]), 0x3F803F80u);
  }
#pragma unroll
  for (int t = 0; t < 8; t++) {
    o[t][0] = o[t][1] = o[t][2] = o[t][3] = 0.f;
    mma16(o[t], pp[(t >> 2) * 2][1], pp[(t >> 2) * 2 + 1][0], z[(t >> 2) * 2], pp[(t >> 2) * 2 + 1][1], kv[16 + 8 * H + t][0], kv[16 + 8 * H + t][1]);
  }
#pragma unroll
  for (int t = 0; t < 8; t++) mma8(o[t], pp[(t >> 2) * 2][0], z[(t >> 2) * 2 + 1], hl[8 + t]);
}
template <int H> __device__ __forceinline__ void att_out(Att& s, uint32_t* of, const Ctx& c, Con& k) {
  auto& o = s.o; auto& dn = s.dn;
  const uint32_t oa = k.stg + H * 8192 + (k.w * 16 + (k.lane & 15)) * 128;
#pragma unroll
  for (int u = 0; u < 4; u++) {
    const float r0 = rcp(dn[u >> 1][0]), r1 = rcp(dn[u >> 1][2]);
#pragma unroll
    for (int e = 0; e < 4; e++) of[4 * u + e] = pack2(o[2 * u + (e >> 1)][2 * (e & 1)] * ((e & 1) ? r1 : r0), o[2 * u + (e >> 1)][2 * (e & 1) + 1] * ((e & 1) ? r1 : r0));
    stsm4(oa + (((2 * u + (k.lane >> 4)) ^ (k.lane & 7)) << 4), of[4 * u], of[4 * u + 1], of[4 * u + 2], of[4 * u + 3]);
  }
  handoff(c, k, H == 0 ? B_SFA : B_SFULL);
  if (k.lane == 0) {
    const uint32_t peer = mapa(c.sb, c.rank ^ 1);
    bulk_s2s(peer + (2 + H) * 32768 + k.wg * 8192 + k.w * 2048, k.stg + H * 8192 + k.w * 2048, 2048, peer + OFF_BAR + 8 * (2 + H));
  }
}

__device__ __forceinline__ void res_load(uint32_t (&res)[32], uint32_t bar, uint32_t par, Con& k) {
  mbar_wait_u(bar, par, k.spin);
#pragma unroll
  for (int u = 0; u < 8; u++)
    ldsm4(k.stg + (u >> 2) * 8192 + (k.w * 16 + (k.lane & 15)) * 128 + ((((2 * u & 7) + (k.lane >> 4)) ^ (k.lane & 7)) << 4), res[4 * u], res[4 * u + 1], res[4 * u + 2], res[4 * u + 3]);
}
__device__ __forceinline__ void res_unpack(float (&rf)[64], const uint32_t (&res)[32]) {
#pragma unroll
  for (int x = 0; x < 32; x++) { rf[2 * x] = bf_lo(res[x]); rf[2 * x + 1] = bf_hi(res[x]); }
  if (PREU) reg_fence(rf);
}
template <int CH> __device__ __forceinline__ void epi_res(const float (&acc)[64], const float (&rf)[64], uint32_t (&res)[32], float sc0, float sc1, Con& k) {
  const uint32_t oa = k.stg + CH * 8192 + (k.w * 16 + (k.lane & 15)) * 128;
#pragma unroll
  for (int u = 0; u < 4; u++) {
#pragma unroll
    for (int e = 0; e < 4; e++) {
      const int x = 16 * CH + 4 * u + e;
      const float sc = (e & 1) ? sc1 : sc0;
      res[x] = pack2(fmaf(sc, acc[2 * x], rf[2 * x]), fmaf(sc, acc[2 * x + 1], rf[2 * x + 1]));
    }
    stsm4(oa + (((2 * u + (k.lane >> 4)) ^ (k.lane & 7)) << 4), res[16 * CH + 4 * u], res[16 * CH + 4 * u + 1], res[16 * CH + 4 * u + 2], res[16 * CH + 4 * u + 3]);
  }
}

template <int NCH, int C0, int C1> __device__ __forceinline__ void epi_ffn1(const float (&acc)[NCH * 32], Pre& a, const Ctx& c, Con& k) {
  const uint32_t csa = c.sb + OFF_CS + (NCH == 4 ? 0 : 1024) + (k.lane & 3) * 16;
  const uint32_t rowo = (k.w * 16 + (k.lane & 15)) * 128;
#pragma unroll
  for (int x = C0; x < C1; x++) {
    const int u = NCH == 4 ? x ^ ROT3 : x, ch = u >> 2, t = 8 * u;
    const uint32_t cb = ch < 2 ? k.stg + ch * 8192 : c.sb + OFF_SPARE + k.wg * 8192 + (ch == NCH - 1 ? 16384 : 0);
    const float4 s = a.cs[u & 3];
    const uint32_t v0 = pack2_relu(fmaf(a.s0.x, s.x, acc[t]), fmaf(a.s0.x, s.y, acc[t + 1])), v1 = pack2_relu(fmaf(a.s1.x, s.x, acc[t + 2]), fmaf(a.s1.x, s.y, acc[t + 3]));
    const uint32_t v2 = pack2_relu(fmaf(a.s0.x, s.z, acc[t + 4]), fmaf(a.s0.x, s.w, acc[t + 5])), v3 = pack2_relu(fmaf(a.s1.x, s.z, acc[t + 6]), fmaf(a.s1.x, s.w, acc[t + 7]));
    if (x + 4 < NCH * 4) a.cs[u & 3] = lds128f(csa + (NCH == 4 ? (x + 4) ^ ROT3 : x + 4) * 64);
    stsm4(cb + rowo + ((((2 * u & 7) + (k.lane >> 4)) ^ (k.lane & 7)) << 4), v0, v1, v2, v3);
  }
  if (C1 == 4 * NCH) handoff(c, k);
}

__device__ __forceinline__ void acc_stat(uint32_t v, float sh, float& s1, float& s2) {
  const float x = bf_lo(v) - sh, y = bf_hi(v) - sh;
  s1 += x + y; s2 = fmaf(y, y, fmaf(x, x, s2));
}
template <bool PF> __device__ __forceinline__ void unit_load(const Params& p, int j, int u, uint32_t dst, uint32_t bar) {
  const int ch = u >> 3;
  const CUtensorMap* mp = ch < 6 ? &p.mCq : &p.mC1;
  const int col = ch < 6 ? (ch < 4 ? 1024 + (ch >> 1) * 1024 : 0) + 128 * j + 64 * (ch & 1) : 448 * j + 64 * (ch - 6);
  if (PF) {
    asm volatile("cp.async.bulk.prefetch.tensor.2d.L2.global [%0, {%1, %2}];" ::"l"(mp), "r"(col), "r"((u & 7) * 128) : "memory");
  } else {
    mbar_expect_tx(bar, 16384);
    tma2d(dst, mp, bar, col, (u & 7) * 128);
  }
}
__device__ __forceinline__ void unit_sum(int j, uint32_t tag, int u, uint32_t src, int lane) {
  float s[8];
#pragma unroll
  for (int e = 0; e < 8; e++) s[e] = 0.f;
  uint4 v[2][4];
#pragma unroll
  for (int e = 0; e < 4; e++) v[0][e] = lds128(src + e * 512 + lane * 16);
#pragma unroll 1
  for (int b = 0; b < 4; b++) {
#pragma unroll
    for (int h = 0; h < 2; h++) {
#pragma unroll
      for (int e = 0; e < 4; e++) v[h ^ 1][e] = lds128(src + ((2 * b + h + 1) & 7) * 2048 + e * 512 + lane * 16);
#pragma unroll
      for (int e = 0; e < 4; e++) {
        const uint4 t = v[h][e];
        s[0] += bf_lo(t.x); s[1] += bf_hi(t.x); s[2] += bf_lo(t.y); s[3] += bf_hi(t.y);
        s[4] += bf_lo(t.z); s[5] += bf_hi(t.z); s[6] += bf_lo(t.w); s[7] += bf_hi(t.w);
      }
    }
  }
  const bool hi = lane & 16, md = lane & 8;
#pragma unroll
  for (int e = 0; e < 4; e++) s[e] = (hi ? s[e + 4] : s[e]) + __shfl_xor_sync(~0u, hi ? s[e] : s[e + 4], 16);
#pragma unroll
  for (int e = 0; e < 2; e++) s[e] = (md ? s[e + 2] : s[e]) + __shfl_xor_sync(~0u, md ? s[e] : s[e + 2], 8);
  st_tag2(g_cs + ((u & 7) * 8 + j) * 832 + (u >> 3) * 64 + (lane & 7) * 8 + (lane >> 4) * 4 + (md ? 2 : 0), s[0], s[1], tag);
}
__device__ __forceinline__ void cs_gather(const Ctx& c, int col, int dcol) {
  float4 v[8]; uint32_t bad; int it = 0;
  do {
    bad = 0;
#pragma unroll
    for (int u = 0; u < 8; u++) v[u] = ld_tag4(g_cs + (u * 8 + c.j) * 832 + col);
#pragma unroll
    for (int u = 0; u < 8; u++) bad |= tag_bad(v[u], c.ep1);
    spin_check(it);
  } while (bad);
#pragma unroll
  for (int u = 1; u < 8; u++) { v[0].x += v[u].x; v[0].y += v[u].y; v[0].z += v[u].z; v[0].w += v[u].w; }
  const uint32_t da = c.sb + OFF_CS + (dcol >> 4) * 64 + (dcol & 4) * 8 + (dcol & 8);
  sts64f(da, v[0].x, v[0].y); sts64f(da + 16, v[0].z, v[0].w);
}
__device__ __forceinline__ void halo_relay(const Ctx& c, int T, int a, int lane) {
  uint32_t hl[16];
#pragma unroll
  for (int u = 0; u < 16; u++) hl[u] = 0;
  if (c.i > 0) {
    const uint4* hp = g_halo + ((((c.i - 1) * 8 + c.j) * 2 + a) * 2 + T) * 256 + lane;
    int it = 0; bool ok;
    do {
      ok = true;
#pragma unroll
      for (int u = 0; u < 8; u++) {
        unsigned long long x, y;
        asm volatile("ld.relaxed.gpu.global.v2.b64 {%0, %1}, [%2];" : "=l"(x), "=l"(y) : "l"(hp + u * 32) : "memory");
        hl[2 * u] = (uint32_t)x; hl[2 * u + 1] = (uint32_t)y;
        ok = ok && (uint32_t)(x >> 32) == c.ep1 && (uint32_t)(y >> 32) == c.ep1;
      }
      spin_check(it);
    } while (!ok);
  }
#pragma unroll
  for (int u = 0; u < 4; u++) sts128(c.sb + OFF_STG + a * 16384 + T * 8192 + lane * 16 + u * 512, hl[4 * u], hl[4 * u + 1], hl[4 * u + 2], hl[4 * u + 3]);
}

__device__ __forceinline__ void aux_warp(const Params& p, const Ctx& c, int a, int lane) {
  const uint32_t spare = c.sb + OFF_SPARE, mystg = c.sb + OFF_STG + a * 16384;
  const uint32_t bA = c.bar + 8 * (B_AUX + a), bSF = c.bar + 8 * (B_SFULL + a), bSE = c.bar + 8 * (B_SEMPTY + a);
  const bool lead = (a == 0 && lane == 0);
  const int row0 = 128 * c.i + 64 * a, u0 = 2 * c.i + a;
  const uint32_t tag = c.ep1 & 3, peer = mapa(c.sb, c.rank ^ 1);
  if (lane == 0) {
    if (a == 0) {
      wait_progress(c, 0);
#pragma unroll
      for (int s = 2; s < 13; s++) map_prefetch(&p.mX + s);
    }
    wait_progress(c, AUX_GATE);
    unit_load<false>(p, c.j, u0, mystg, bA);
  }
  mbar_wait(bA, 0);
  if (lead) PROF(4);
  unit_sum(c.j, tag, u0, mystg, lane);
  if (lead) PROF(6);
  wait_progress(c, G0);
  {
    float4 v; int it = 0;
    do { v = ld_tag4(g_xst + (64 * c.i + 32 * a + lane) * 4); spin_check(it); } while (tag_bad(v, tag));
    sts64f(c.sb + OFF_ST + (32 * a + lane) * 8, v.x, v.y); sts64f(c.sb + OFF_ST + (64 + 32 * a + lane) * 8, v.z, v.w);
  }
#pragma unroll 1
  for (int r = 0; r < 4; r++) {
    if (r == 2) {
      if (lane == 0) {
        mbar_wait(c.bar + 8 * (B_SFA + a), 1);
        tma2d_st(&p.mH, mystg, 128 * c.j, row0); bulk_commit();
        if (lead) PROF(18);
        wait_empty(c, 46);
        bulk_s2s(peer + 1 * 49152 + a * 8192, mystg, 8192, peer + OFF_BAR + 8 * (50 & 7));
        bulk_wait_all(); flag_add(F_H + c.i * 4 + a);
        if (lead) PROF(19);
        mbar_wait(bSF, 1);
        wait_empty(c, 47);
        bulk_s2s(peer + 2 * 49152 + a * 8192, mystg + 8192, 8192, peer + OFF_BAR + 8 * (51 & 7));
        wait_progress(c, 48 + PACEH + a);
        tma2d_st(&p.mH, mystg + 8192, 128 * c.j + 64, row0); bulk_commit();
        bulk_wait_all(); flag_add(F_H + c.i * 4 + 2 + a);
        if (lead) PROF(20);
      }
      __syncwarp();
      if (lane == 0) mbar_arrive(bSE);
      if (lead) PROF(12);
      wait_progress(c, GS);
      {
        float4 v[8]; uint32_t bad; int it = 0;
        do {
          bad = 0;
#pragma unroll
          for (int u = 0; u < 8; u++) v[u] = ld_tag4(g_hst + row0 * 8 + u * 64 + 2 * lane);
#pragma unroll
          for (int u = 0; u < 8; u++) bad |= tag_bad(v[u], tag);
          spin_check(it);
        } while (bad);
        float m0 = 0.f, m1 = 0.f, q0 = 0.f, q1 = 0.f;
#pragma unroll
        for (int u = 0; u < 8; u++) { m0 += v[u].x; m1 += v[u].z; }
        m0 *= 0.125f; m1 *= 0.125f;
#pragma unroll
        for (int u = 0; u < 8; u++) { q0 += fmaf(128.f * (v[u].x - m0), v[u].x - m0, v[u].y); q1 += fmaf(128.f * (v[u].z - m1), v[u].z - m1, v[u].w); }
        sts128(c.sb + OFF_ST + (64 * a + 2 * lane) * 8, __float_as_uint(m0), __float_as_uint(rsqrtf(fmaxf(q0, 0.f) * (1.f / D_) + 1e-5f)),
               __float_as_uint(m1), __float_as_uint(rsqrtf(fmaxf(q1, 0.f) * (1.f / D_) + 1e-5f)));
      }
    }
    const int nl = r == 1 ? 16 : r == 3 ? 24 : 32, dcol = 256 * (r & 1) + 4 * (nl * a + lane);
    if (lane < nl) cs_gather(c, dcol + 384 * (r >> 1), dcol);
    __syncwarp();
    if (lane == 0) { mbar_arrive(c.bar + 8 * (B_RDY0 + (r & 1))); if (lead) PROF(7 + r); }
    if (r == 1) {
      wait_progress(c, GH);
#pragma unroll 1
      for (int t = 0; t < 2; t++) halo_relay(c, t, a, lane);
      __syncwarp();
      if (lane == 0) {
        mbar_arrive(c.bar + 8 * (B_HALO + a));
        if (lead) PROF(11);
#pragma unroll 1
        for (int t = 0; t < 2; t++) {
          mbar_wait(t ? bSF : c.bar + 8 * (B_SFA + a), 0);
          tma2d_st(&p.mO, mystg + t * 8192, 128 * c.j + 64 * t, row0); bulk_commit();
          if (lead) PROF(13 + 3 * t);
          bulk_wait_all(); flag_add(F_O + c.i * 4 + 2 * t + a);
          if (lead) PROF(14 + 3 * t);
        }
        wait_progress(c, XR + a * XRA);
        mbar_expect_tx(bSE, 16384);
        tma3d(mystg, &p.mX, bSE, 128 * c.j, a, 64 * c.i); tma3d(mystg + 8192, &p.mX, bSE, 128 * c.j + 64, a, 64 * c.i);
      }
      named_sync(3, 64);
    }
    if (r >= 2) {
      if (lane == 0) {
        const int col = 448 * c.j + 256 * (r - 2);
        mbar_wait(bSF, r & 1);
#pragma unroll 1
        for (int x = r - 2; x < 4; x++) {
          wait_progress(c, r == 2 ? 64 + PACE3 + 2 * x + a : 80 + PACE4 + PACE * (2 * (x - 1) + a));
          tma2d_st(&p.mH1, x < 2 ? spare + x * 16384 + a * 8192 : mystg + (x - 2) * 8192, col + (x < 2 ? (x + 4 - r) * 64 : (x - 2) * 64), row0);
          bulk_commit();
          if (x == 7 - 2 * r) { bulk_wait_read(); mbar_arrive(bSE); }
        }
        bulk_wait_all(); flag_add(F_H1 + c.i * 4 + 2 * (r - 2) + a);
        if (lead) PROF(20 + r);
        if (r == 3) { mbar_expect_tx(bA, 16384); tma2d(mystg, &p.mH, bA, 128 * c.j, row0); tma2d(mystg + 8192, &p.mH, bA, 128 * c.j + 64, row0); }
      }
      __syncwarp();
    }
  }
}

__device__ __forceinline__ void helper_unit(int g, int& j, int& u) {
  const int x = g >> 3;
  j = x < 16 ? x >> 1 : x < 48 ? (x - 16) >> 2 : (x - 48) / 3;
  u = 8 * (x < 16 ? 4 + (x & 1) : x < 48 ? 6 + (x & 3) : 10 + x % 3) + (g & 7);
}
__device__ __forceinline__ void helper_warp(const Params& p, const Ctx& c, int g0, int warp, int lane) {
  const uint32_t buf = c.sb + warp * 16384, bar = c.bar + 8 * (warp < 8 ? warp : warp + B_SEMPTY - 8);
#pragma unroll 1
  for (int t = 0; t < 12; t++) {
    int j, u;
    if (t < 11 && lane == 0) { helper_unit(g0 + 48 * t + 48, j, u); unit_load<true>(p, j, u, 0, 0); }
    helper_unit(g0 + 48 * t, j, u);
    if (lane == 0) unit_load<false>(p, j, u, buf, bar);
    mbar_wait(bar, t & 1);
    unit_sum(j, c.ep1 & 3, u, buf, lane);
  }
}

__device__ __forceinline__ uint32_t load_epoch() {
  uint32_t ctr;
  asm volatile("ld.relaxed.gpu.global.u32 %0, [%1];" : "=r"(ctr) : "l"(&g_ctr) : "memory");
  return (ctr >> 7) + 1;
}

__global__ void __cluster_dims__(2, 1, 1) __launch_bounds__(384, 1) fused_block_kernel(const __grid_constant__ Params p) {
  extern __shared__ __align__(1024) uint8_t smem_raw[];
  Ctx c;
  c.sb = (uint32_t)__cvta_generic_to_shared(smem_raw);
  c.bar = c.sb + OFF_BAR;
  c.rank = blockIdx.x & 1;
  int cl = (blockIdx.x >> 1) + (gridDim.x == 4 ? 64 : 0);
  if (gridDim.x == 132) {
    uint32_t t; asm("mov.u32 %0, %%smid;" : "=r"(t));
    t >>= 1;
    cl = t < 32 ? (t & 7) * 8 + (t >> 3) : t < 60 ? (1 + (t - 32) % 7) * 8 + 4 + (t - 32) / 7 : t < 62 ? t + 4 : t - 58;
  }
  const bool helper = cl >= 64;
  c.i = cl & 15; c.j = ((cl >> 4) & 3) * 2 + c.rank;
  const int warp = __shfl_sync(~0u, threadIdx.x >> 5, 0), lane = threadIdx.x & 31;
  if (warp == 8 && lane == 0) {
    PROF(0);
    map_prefetch(&p.mWkv); map_prefetch(&p.mX);
#pragma unroll
    for (int s = 0; s < 4; s++) mbar_init(c.bar + 8 * s, 1);
    fence_async_smem();
    if (!helper) produce_b<0>(p, c, 0, NB0);
    asm volatile("fence.mbarrier_init.release.cluster;" ::: "memory");
  }
  if (warp == 9 && lane == 0) {
    asm volatile("{\n.reg .pred p;\nsetp.ne.u32 p, %0, %1;\n@p trap;\n}\n" ::"r"(c.sb & 0x3FFFF), "n"(SMEM_BASE));
#pragma unroll
    for (int s = 4; s < B_NUM; s++) mbar_init(c.bar + 8 * s, (s < B_EMPTY || s >= B_SEMPTY) ? 1 : (s >= B_RDY0 ? 2 : 4));
    set_progress(c, -1); __threadfence_block();
    asm volatile("fence.mbarrier_init.release.cluster;" ::: "memory");
    fence_async_smem();
  }
  __syncwarp();
  asm volatile("barrier.cluster.arrive.relaxed.aligned;" ::: "memory");
  asm volatile("barrier.cluster.wait.acquire.aligned;" ::: "memory");
  if (helper) {
    c.ep1 = load_epoch();
    helper_warp(p, c, ((cl & 1) * 2 + c.rank) * 12 + warp, warp, lane);
  } else if (warp >= 8) {
    asm volatile("setmaxnreg.dec.sync.aligned.u32 88;");
    if (warp == 8) {
      if (lane == 0) {
        PROF(1);
        produce_b<0>(p, c, NB0, 16); produce_b<1>(p, c, 0, 16); produce_b<2>(p, c, 0, 16); produce_b<3>(p, c, 0, 16); produce_b<4>(p, c, 0, 16); produce_b<5>(p, c, 0, 56);
        asm volatile("red.relaxed.gpu.global.add.u32 [%0], 1;" ::"l"(&g_ctr) : "memory");
      }
    } else if (warp == 9) {
      if (lane == 0) {
        bool seen = false;
        produce_a<0>(p, c, seen); c.ep1 = load_epoch(); produce_a<1>(p, c, seen); produce_a<2>(p, c, seen); produce_a<3>(p, c, seen); produce_a<4>(p, c, seen); produce_a<5>(p, c, seen);
      }
    } else {
      c.ep1 = load_epoch();
      aux_warp(p, c, warp - 10, lane);
    }
  } else {
    asm volatile("setmaxnreg.inc.sync.aligned.u32 208;");
    c.ep1 = load_epoch();
    Con k;
    k.wg = warp >> 2; k.w = warp & 3; k.lane = lane; k.spin = 0;
    k.do_rel = (threadIdx.x & 127) < 2;
    k.rel = mapa(c.bar + 8 * B_EMPTY, threadIdx.x & 1);
    k.stg = c.sb + OFF_STG + k.wg * 16384;
    k.da = ((SMEM_BASE >> 4) | (1u << 16)) + k.wg * 512;
    uint32_t kv[32][2], res[32]; float accq[64];
    {
      float acc[128]; Pre pr;
      const int rb = 16 * c.j + 2 * warp + (lane >> 4);
      const uint4* xr = reinterpret_cast<const uint4*>(p.x + (size_t)(128 * c.i + rb) * D_) + (lane & 15);
      uint4 xv[8];
      ISSUE0(0, acc);
#pragma unroll
      for (int e = 0; e < 8; e++) xv[e] = ldcg128(xr + 16 * e);
      steps<0>(acc, c, k, 1, XST);
      ISSUE(0, acc, XST);
      const float sh = XSH ? __shfl_sync(~0u, bf_lo(xv[0].x), lane & 16) : 0.f;
      float s1[2] = {0.f, 0.f}, s2[2] = {0.f, 0.f};
#pragma unroll
      for (int e = 0; e < 8; e++) {
        { acc_stat(xv[e].x, sh, s1[0], s2[0]); acc_stat(xv[e].y, sh, s1[1], s2[1]); acc_stat(xv[e].z, sh, s1[0], s2[0]); acc_stat(xv[e].w, sh, s1[1], s2[1]); }
        if (XS3 ? (e & 3) == 3 : e == 4) { asm volatile("" : "+f"(s1[0]), "+f"(s1[1]), "+f"(s2[0]), "+f"(s2[1])); retire<0>(k, XST + (XS3 ? e >> 2 : 0)); ISSUE(0, acc, XST + 1 + (XS3 ? e >> 2 : 0)); }
      }
      float t1 = s1[0] + s1[1], t2 = s2[0] + s2[1];
#pragma unroll
      for (int o = 1; o < 16; o <<= 1) { t1 += __shfl_xor_sync(~0u, t1, o); t2 += __shfl_xor_sync(~0u, t2, o); }
      t1 *= 1.f / D_;
      if ((lane & 15) < 2) st_tag2(g_xst + (64 * c.i + (rb >> 1)) * 4 + 2 * (lane & 1) + (rb & 1), sh + t1, rsqrtf(fmaxf(fmaf(-t1, t1, t2 * (1.f / D_)), 0.f) + 1e-5f), c.ep1 & 3);
      if (threadIdx.x == 0) PROF(5);
      retire<0>(k, XST + 1 + XS3);
      steps<0>(acc, c, k, XST + 2 + XS3, 15);
      LAST(0, acc, (STAG & 1));
      qkv_pack<0, 0, SH0 ? 8 : 16>(kv, acc, pr, c, k);
      ISSUE0(1, accq);
      if (SH0) {
        qkv_pack<0, 8, 10>(kv, acc, pr, c, k);
        ISSUE(1, accq, 1); qkv_pack<0, 10, 12>(kv, acc, pr, c, k); retire<1>(k, 1);
        ISSUE(1, accq, 2); qkv_pack<0, 12, 14>(kv, acc, pr, c, k); retire<1>(k, 2);
        ISSUE(1, accq, 3); qkv_pack<0, 14, 16>(kv, acc, pr, c, k); retire<1>(k, 3);
      }
      if (k.do_rel) PROF(32 + 32 * k.wg + 2);
    }
    {
      float (&acc)[64] = accq; Pre pr; uint32_t q[16][2];
      constexpr int M = 1 + 3 * SH0;
      ISSUE(1, acc, M);
#pragma unroll
      for (int t = 16; t < 32; t++) kv[t][1] = movm(kv[t][1]);
      retire<1>(k, M);
      ISSUE(1, acc, M + 1); halo_publish<0>(kv, c, k); retire<1>(k, M + 1);
      ISSUE(1, acc, M + 2); halo_publish<1>(kv, c, k); retire<1>(k, M + 2);
      steps<1>(acc, c, k, M + 3, 15);
      ISSUE(1, acc, 15); pre_load<1>(pr, c, k);
      const float sc0 = pr.s0.y * 0.25503487f, sc1 = pr.s1.y * 0.25503487f;
      const float lmask = -1.4426950408889634e9f * rcp(sc0);
      Att s0, s1;
      att_halo<0>(s0, k);
      retire<1>(k, 15);
      mbar_wait_u(c.bar + 8 * (B_EMPTY + 5), 1, k.spin);
      finish<1>(k);
      qkv_pack<1, 0, 4>(q, acc, pr, c, k);
      att_qk<0>(s0, q, kv, lmask, c, k); att_soft(s0, sc0, sc1, k); att_pv<0>(s0, kv);
      att_out<0>(s0, res, c, k);
      att_halo<1>(s1, k);
      qkv_pack<1, 4, 8>(q, acc, pr, c, k);
      att_qk<1>(s1, q, kv, lmask, c, k); att_soft(s1, sc0, sc1, k); att_pv<1>(s1, kv);
      att_out<1>(s1, res + 16, c, k);
      if (k.do_rel) PROF(32 + 32 * k.wg + 5);
    }
    {
      float acc[64];
      ISSUE_RS(2, acc, res);
      steps<2>(acc, c, k, 2, 15 - PREU);
      ISSUE(2, acc, 15 - PREU);
      float rf[64];
      res_load(res, c.bar + 8 * (B_SEMPTY + k.wg), 0, k); res_unpack(rf, res);
      if (PREU) { retire<2>(k, 14); ISSUE(2, acc, 15); }
      retire<2>(k, 15);
      finish<2>(k);
      epi_res<0>(acc, rf, res, 1.f, 1.f, k);
      handoff(c, k, B_SFA);
      epi_res<1>(acc, rf, res, 1.f, 1.f, k);
      handoff(c, k);
      if (k.do_rel) PROF(32 + 32 * k.wg + 8);
    }
    {
      float acc4[96], acc[64]; Pre pr;
      {
        float acc3[128];
        ISSUE_RS(3, acc3, res);
        ISSUE(3, acc3, 2); retire<3>(k, 2);
        float s1[2] = {0.f, 0.f}, s2[2] = {0.f, 0.f};
        ISSUE(3, acc3, 3);
#pragma unroll
        for (int e = 0; e < 32; e++) {
          acc_stat(res[e], 0.f, s1[e & 1], s2[e & 1]);
          if (e == 19) { asm volatile("" : "+f"(s1[0]), "+f"(s1[1]), "+f"(s2[0]), "+f"(s2[1])); retire<3>(k, 3); ISSUE(3, acc3, 4); }
        }
        const bool odd = lane & 1;
        float t1 = (odd ? s1[1] : s1[0]) + __shfl_xor_sync(~0u, odd ? s1[0] : s1[1], 1), t2 = (odd ? s2[1] : s2[0]) + __shfl_xor_sync(~0u, odd ? s2[0] : s2[1], 1);
        t1 += __shfl_xor_sync(~0u, t1, 2); t2 += __shfl_xor_sync(~0u, t2, 2);
        if (!(lane & 2)) st_tag2(g_hst + (128 * c.i + 64 * k.wg) * 8 + c.j * 64 + k.w * 16 + (lane >> 2) + 8 * (lane & 1), t1 * (1.f / 128), fmaf(-t1 * (1.f / 128), t1, t2), c.ep1 & 3);
        retire<3>(k, 4);
        steps<3>(acc3, c, k, 5, 15);
        LAST(3, acc3, (STAG & 2));
        if (SH3) {
          epi_ffn1<4, 0, 8>(acc3, pr, c, k);
          ISSUE0(4, acc4); epi_ffn1<4, 8, 10>(acc3, pr, c, k);
          ISSUE(4, acc4, 1); epi_ffn1<4, 10, 13>(acc3, pr, c, k); retire<4>(k, 1);
          ISSUE(4, acc4, 2); epi_ffn1<4, 13, 16>(acc3, pr, c, k); retire<4>(k, 2);
        } else {
          epi_ffn1<4, 0, 16>(acc3, pr, c, k);
          ISSUE0(4, acc4);
        }
        if (k.do_rel) PROF(32 + 32 * k.wg + 11);
      }
      steps<4>(acc4, c, k, SH3 ? 3 : 1, 15);
      ISSUE(4, acc4, 15); pre_load<4>(pr, c, k); retire<4>(k, 15);
      if (SH4) {
        ISSUE0(5, acc);
        finish<4, 1>(k);
        reg_fence(acc4);
        ISSUE(5, acc, 1); epi_ffn1<3, 0, 2>(acc4, pr, c, k); retire<5>(k, 1);
        ISSUE(5, acc, 2); epi_ffn1<3, 2, 4>(acc4, pr, c, k); retire<5>(k, 2);
        ISSUE(5, acc, 3); epi_ffn1<3, 4, 6>(acc4, pr, c, k); retire<5>(k, 3);
        ISSUE(5, acc, 4); epi_ffn1<3, 6, 8>(acc4, pr, c, k); retire<5>(k, 4);
        ISSUE(5, acc, 5); epi_ffn1<3, 8, 10>(acc4, pr, c, k); retire<5>(k, 5);
        ISSUE(5, acc, 6); epi_ffn1<3, 10, 12>(acc4, pr, c, k); retire<5>(k, 6);
      } else {
        finish<4>(k);
        epi_ffn1<3, 0, 12>(acc4, pr, c, k);
        ISSUE0(5, acc);
      }
      if (k.do_rel) PROF(32 + 32 * k.wg + 14);
      steps<5>(acc, c, k, SH4 ? 7 : 1, 55 - PREU);
      ISSUE(5, acc, 55 - PREU);
      const uint32_t sta = c.sb + OFF_ST + (k.wg * 64 + k.w * 16 + (lane >> 2)) * 8;
      const float sc0 = lds64f(sta).y, sc1 = lds64f(sta + 64).y;
      float rf[64];
      res_load(res, c.bar + 8 * (B_AUX + k.wg), 1, k); res_unpack(rf, res);
      if (PREU) ISSUE(5, acc, 55);
      spin_check(k.spin);
      finish<5>(k);
      epi_res<0>(acc, rf, res, sc0, sc1, k);
      fence_async_smem(); __syncwarp();
      if (lane == 0) tma3d_st(&p.mOut, k.stg + k.w * 2048, 128 * c.j, k.wg, 64 * c.i + 16 * k.w);
      epi_res<1>(acc, rf, res, sc0, sc1, k);
      fence_async_smem(); __syncwarp();
      if (k.do_rel) PROF(32 + 32 * k.wg + 17);
      if (lane == 0) { tma3d_st(&p.mOut, k.stg + 8192 + k.w * 2048, 128 * c.j + 64, k.wg, 64 * c.i + 16 * k.w); bulk_commit(); bulk_wait_read(); }
      if (k.do_rel) PROF(32 + 32 * k.wg + 18);
    }
  }
}

typedef CUresult (*EncFn)(CUtensorMap*, CUtensorMapDataType, cuuint32_t, void*, const cuuint64_t*, const cuuint64_t*, const cuuint32_t*,
                          const cuuint32_t*, CUtensorMapInterleave, CUtensorMapSwizzle, CUtensorMapL2promotion, CUtensorMapFloatOOBfill);

void enc(EncFn f, CUtensorMap* m, const void* ptr, int rank, cuuint64_t d0, cuuint64_t d1, cuuint64_t d2, cuuint64_t s1, cuuint64_t s2,
         cuuint32_t b0, cuuint32_t b1, cuuint32_t b2, CUtensorMapSwizzle sw = CU_TENSOR_MAP_SWIZZLE_128B) {
  const cuuint64_t dims[3] = {d0, d1, d2}, str[2] = {s1, s2};
  const cuuint32_t box[3] = {b0, b1, b2}, es[3] = {1, 1, 1};
  f(m, CU_TENSOR_MAP_DATA_TYPE_BFLOAT16, rank, const_cast<void*>(ptr), dims, str, box, es, CU_TENSOR_MAP_INTERLEAVE_NONE,
    sw, CU_TENSOR_MAP_L2_PROMOTION_L2_256B, CU_TENSOR_MAP_FLOAT_OOB_FILL_NONE);
}

}

extern "C" void kernel_launch(void* const* d_in, const int* in_sizes, int n_in, void* d_out, int out_size) {
  (void)in_sizes; (void)n_in; (void)out_size;
  const void *x = d_in[0], *wqkv = d_in[1], *wo = d_in[2], *w1 = d_in[4], *w2 = d_in[5];
  EncFn f = nullptr;
  cudaDriverEntryPointQueryResult qr;
  cudaGetDriverEntryPoint("cuTensorMapEncodeTiled", (void**)&f, cudaEnableDefault, &qr);
  void *po, *ph, *ph1;
  cudaGetSymbolAddress(&po, g_o); cudaGetSymbolAddress(&ph, g_h); cudaGetSymbolAddress(&ph1, g_h1);
  Params p;
  enc(f, &p.mX, x, 3, D_, 2, S_ / 2, D_ * 2, D_ * 4, 64, 1, 64);
  enc(f, &p.mOut, d_out, 3, D_, 2, S_ / 2, D_ * 2, D_ * 4, 64, 1, 16);
  enc(f, &p.mCq, wqkv, 2, 3 * D_, D_, 1, 3 * D_ * 2, 0, 64, 128, 1, CU_TENSOR_MAP_SWIZZLE_NONE);
  enc(f, &p.mC1, w1, 2, F_, D_, 1, F_ * 2, 0, 64, 128, 1, CU_TENSOR_MAP_SWIZZLE_NONE);
  {
    const cuuint64_t dims[4] = {64, D_, D_ / 64, 3}, str[3] = {3 * D_ * 2, 128, D_ * 2};
    const cuuint32_t box[4] = {64, 64, 2, 2}, es[4] = {1, 1, 1, 1};
    f(&p.mWkv, CU_TENSOR_MAP_DATA_TYPE_BFLOAT16, 4, const_cast<void*>(wqkv), dims, str, box, es, CU_TENSOR_MAP_INTERLEAVE_NONE,
      CU_TENSOR_MAP_SWIZZLE_128B, CU_TENSOR_MAP_L2_PROMOTION_L2_256B, CU_TENSOR_MAP_FLOAT_OOB_FILL_NONE);
  }
  enc(f, &p.mWq, wqkv, 3, 64, D_, D_ / 64, 3 * D_ * 2, 128, 64, 64, 2);
  enc(f, &p.mWo, wo, 3, 64, D_, D_ / 64, D_ * 2, 128, 64, 64, 2);
  enc(f, &p.mW1a, w1, 3, 64, D_, F_ / 64, F_ * 2, 128, 64, 64, 4);
  enc(f, &p.mW1b, w1, 3, 64, D_, F_ / 64, F_ * 2, 128, 64, 64, 3);
  enc(f, &p.mW2, w2, 3, 64, F_, D_ / 64, D_ * 2, 128, 64, 64, 2);
  enc(f, &p.mO, po, 2, D_, S_, 1, D_ * 2, 0, 64, 64, 1);
  enc(f, &p.mH, ph, 2, D_, S_, 1, D_ * 2, 0, 64, 64, 1);
  enc(f, &p.mH1, ph1, 2, F_, S_, 1, F_ * 2, 0, 64, 64, 1);
  p.x = (const bf16*)x;
  cudaFuncSetAttribute(fused_block_kernel, cudaFuncAttributeMaxDynamicSharedMemorySize, SMEM_BYTES);
  cudaLaunchConfig_t cfg = {};
  cudaLaunchAttribute at;
  at.id = cudaLaunchAttributeClusterDimension; at.val.clusterDim.x = 2; at.val.clusterDim.y = 1; at.val.clusterDim.z = 1;
  cfg.gridDim = dim3(132); cfg.blockDim = dim3(384); cfg.dynamicSmemBytes = SMEM_BYTES; cfg.attrs = &at; cfg.numAttrs = 1;
  int ncl = 0;
  cudaOccupancyMaxActiveClusters(&ncl, fused_block_kernel, &cfg);
  if (ncl >= 66) {
    fused_block_kernel<<<132, 384, SMEM_BYTES>>>(p);
  } else {
    fused_block_kernel<<<4, 384, SMEM_BYTES>>>(p);
    fused_block_kernel<<<128, 384, SMEM_BYTES>>>(p);
  }
}
```

```cpp
#include <cuda_runtime.h>
#include <cuda_bf16.h>
#include <cuda.h>
#include <stdint.h>

namespace {

template <int FIRST> __device__ __forceinline__ void wgmma4_n128(float (&d)[64], uint32_t a, uint32_t b) {
#define WGD "{%0, %1, %2, %3, %4, %5, %6, %7, %8, %9, %10, %11, %12, %13, %14, %15, %16, %17, %18, %19, %20, %21, %22, %23, %24, %25, %26, %27, %28, %29, %30, %31, %32, %33, %34, %35, %36, %37, %38, %39, %40, %41, %42, %43, %44, %45, %46, %47, %48, %49, %50, %51, %52, %53, %54, %55, %56, %57, %58, %59, %60, %61, %62, %63}"
  asm volatile("{\n.reg .pred p, q;\n.reg .b64 da, db;\n.reg .b32 x, y;\nsetp.eq.b32 p, %66, 0;\nsetp.eq.b32 q, 0, 0;\n"
    "add.s32 x, %64, 0;\nadd.s32 y, %65, 0;\nmov.b64 da, {x, %67};\nmov.b64 db, {y, %67};\n"
    "wgmma.mma_async.sync.aligned.m64n128k16.f32.bf16.bf16 " WGD ", da, db, p, 1, 1, 0, 1;\n"
    "add.s32 x, %64, 2;\nadd.s32 y, %65, 128;\nmov.b64 da, {x, %67};\nmov.b64 db, {y, %67};\n"
    "wgmma.mma_async.sync.aligned.m64n128k16.f32.bf16.bf16 " WGD ", da, db, q, 1, 1, 0, 1;\n"
    "add.s32 x, %64, 4;\nadd.s32 y, %65, 256;\nmov.b64 da, {x, %67};\nmov.b64 db, {y, %67};\n"
    "wgmma.mma_async.sync.aligned.m64n128k16.f32.bf16.bf16 " WGD ", da, db, q, 1, 1, 0, 1;\n"
    "add.s32 x, %64, 6;\nadd.s32 y, %65, 384;\nmov.b64 da, {x, %67};\nmov.b64 db, {y, %67};\n"
    "wgmma.mma_async.sync.aligned.m64n128k16.f32.bf16.bf16 " WGD ", da, db, q, 1, 1, 0, 1;\n"
    "}\n"
    : "+f"(d[0]), "+f"(d[1]), "+f"(d[2]), "+f"(d[3]), "+f"(d[4]), "+f"(d[5]), "+f"(d[6]), "+f"(d[7]),
      "+f"(d[8]), "+f"(d[9]), "+f"(d[10]), "+f"(d[11]), "+f"(d[12]), "+f"(d[13]), "+f"(d[14]), "+f"(d[15]),
      "+f"(d[16]), "+f"(d[17]), "+f"(d[18]), "+f"(d[19]), "+f"(d[20]), "+f"(d[21]), "+f"(d[22]), "+f"(d[23]),
      "+f"(d[24]), "+f"(d[25]), "+f"(d[26]), "+f"(d[27]), "+f"(d[28]), "+f"(d[29]), "+f"(d[30]), "+f"(d[31]),
      "+f"(d[32]), "+f"(d[33]), "+f"(d[34]), "+f"(d[35]), "+f"(d[36]), "+f"(d[37]), "+f"(d[38]), "+f"(d[39]),
      "+f"(d[40]), "+f"(d[41]), "+f"(d[42]), "+f"(d[43]), "+f"(d[44]), "+f"(d[45]), "+f"(d[46]), "+f"(d[47]),
      "+f"(d[48]), "+f"(d[49]), "+f"(d[50]), "+f"(d[51]), "+f"(d[52]), "+f"(d[53]), "+f"(d[54]), "+f"(d[55]),
      "+f"(d[56]), "+f"(d[57]), "+f"(d[58]), "+f"(d[59]), "+f"(d[60]), "+f"(d[61]), "+f"(d[62]), "+f"(d[63])
    : "r"(a), "r"(b), "n"(FIRST), "r"(0x40000040));
#undef WGD
}

template <int FIRST> __device__ __forceinline__ void wgmma4_n192(float (&d)[96], uint32_t a, uint32_t b) {
#define WGD "{%0, %1, %2, %3, %4, %5, %6, %7, %8, %9, %10, %11, %12, %13, %14, %15, %16, %17, %18, %19, %20, %21, %22, %23, %24, %25, %26, %27, %28, %29, %30, %31, %32, %33, %34, %35, %36, %37, %38, %39, %40, %41, %42, %43, %44, %45, %46, %47, %48, %49, %50, %51, %52, %53, %54, %55, %56, %57, %58, %59, %60, %61, %62, %63, %64, %65, %66, %67, %68, %69, %70, %71, %72, %73, %74, %75, %76, %77, %78, %79, %80, %81, %82, %83, %84, %85, %86, %87, %88, %89, %90, %91, %92, %93, %94, %95}"
  asm volatile("{\n.reg .pred p, q;\n.reg .b64 da, db;\n.reg .b32 x, y;\nsetp.eq.b32 p, %98, 0;\nsetp.eq.b32 q, 0, 0;\n"
    "add.s32 x, %96, 0;\nadd.s32 y, %97, 0;\nmov.b64 da, {x, %99};\nmov.b64 db, {y, %99};\n"
    "wgmma.mma_async.sync.aligned.m64n192k16.f32.bf16.bf16 " WGD ", da, db, p, 1, 1, 0, 1;\n"
    "add.s32 x, %96, 2;\nadd.s32 y, %97, 128;\nmov.b64 da, {x, %99};\nmov.b64 db, {y, %99};\n"
    "wgmma.mma_async.sync.aligned.m64n192k16.f32.bf16.bf16 " WGD ", da, db, q, 1, 1, 0, 1;\n"
    "add.s32 x, %96, 4;\nadd.s32 y, %97, 256;\nmov.b64 da, {x, %99};\nmov.b64 db, {y, %99};\n"
    "wgmma.mma_async.sync.aligned.m64n192k16.f32.bf16.bf16 " WGD ", da, db, q, 1, 1, 0, 1;\n"
    "add.s32 x, %96, 6;\nadd.s32 y, %97, 384;\nmov.b64 da, {x, %99};\nmov.b64 db, {y, %99};\n"
    "wgmma.mma_async.sync.aligned.m64n192k16.f32.bf16.bf16 " WGD ", da, db, q, 1, 1, 0, 1;\n"
    "}\n"
    : "+f"(d[0]), "+f"(d[1]), "+f"(d[2]), "+f"(d[3]), "+f"(d[4]), "+f"(d[5]), "+f"(d[6]), "+f"(d[7]),
      "+f"(d[8]), "+f"(d[9]), "+f"(d[10]), "+f"(d[11]), "+f"(d[12]), "+f"(d[13]), "+f"(d[14]), "+f"(d[15]),
      "+f"(d[16]), "+f"(d[17]), "+f"(d[18]), "+f"(d[19]), "+f"(d[20]), "+f"(d[21]), "+f"(d[22]), "+f"(d[23]),
      "+f"(d[24]), "+f"(d[25]), "+f"(d[26]), "+f"(d[27]), "+f"(d[28]), "+f"(d[29]), "+f"(d[30]), "+f"(d[31]),
      "+f"(d[32]), "+f"(d[33]), "+f"(d[34]), "+f"(d[35]), "+f"(d[36]), "+f"(d[37]), "+f"(d[38]), "+f"(d[39]),
      "+f"(d[40]), "+f"(d[41]), "+f"(d[42]), "+f"(d[43]), "+f"(d[44]), "+f"(d[45]), "+f"(d[46]), "+f"(d[47]),
      "+f"(d[48]), "+f"(d[49]), "+f"(d[50]), "+f"(d[51]), "+f"(d[52]), "+f"(d[53]), "+f"(d[54]), "+f"(d[55]),
      "+f"(d[56]), "+f"(d[57]), "+f"(d[58]), "+f"(d[59]), "+f"(d[60]), "+f"(d[61]), "+f"(d[62]), "+f"(d[63]),
      "+f"(d[64]), "+f"(d[65]), "+f"(d[66]), "+f"(d[67]), "+f"(d[68]), "+f"(d[69]), "+f"(d[70]), "+f"(d[71]),
      "+f"(d[72]), "+f"(d[73]), "+f"(d[74]), "+f"(d[75]), "+f"(d[76]), "+f"(d[77]), "+f"(d[78]), "+f"(d[79]),
      "+f"(d[80]), "+f"(d[81]), "+f"(d[82]), "+f"(d[83]), "+f"(d[84]), "+f"(d[85]), "+f"(d[86]), "+f"(d[87]),
      "+f"(d[88]), "+f"(d[89]), "+f"(d[90]), "+f"(d[91]), "+f"(d[92]), "+f"(d[93]), "+f"(d[94]), "+f"(d[95])
    : "r"(a), "r"(b), "n"(FIRST), "r"(0x40000040));
#undef WGD
}

template <int FIRST> __device__ __forceinline__ void wgmma4_n256(float (&d)[128], uint32_t a, uint32_t b) {
#define WGD "{%0, %1, %2, %3, %4, %5, %6, %7, %8, %9, %10, %11, %12, %13, %14, %15, %16, %17, %18, %19, %20, %21, %22, %23, %24, %25, %26, %27, %28, %29, %30, %31, %32, %33, %34, %35, %36, %37, %38, %39, %40, %41, %42, %43, %44, %45, %46, %47, %48, %49, %50, %51, %52, %53, %54, %55, %56, %57, %58, %59, %60, %61, %62, %63, %64, %65, %66, %67, %68, %69, %70, %71, %72, %73, %74, %75, %76, %77, %78, %79, %80, %81, %82, %83, %84, %85, %86, %87, %88, %89, %90, %91, %92, %93, %94, %95, %96, %97, %98, %99, %100, %101, %102, %103, %104, %105, %106, %107, %108, %109, %110, %111, %112, %113, %114, %115, %116, %117, %118, %119, %120, %121, %122, %123, %124, %125, %126, %127}"
  asm volatile("{\n.reg .pred p, q;\n.reg .b64 da, db;\n.reg .b32 x, y;\nsetp.eq.b32 p, %130, 0;\nsetp.eq.b32 q, 0, 0;\n"
    "add.s32 x, %128, 0;\nadd.s32 y, %129, 0;\nmov.b64 da, {x, %131};\nmov.b64 db, {y, %131};\n"
    "wgmma.mma_async.sync.aligned.m64n256k16.f32.bf16.bf16 " WGD ", da, db, p, 1, 1, 0, 1;\n"
    "add.s32 x, %128, 2;\nadd.s32 y, %129, 128;\nmov.b64 da, {x, %131};\nmov.b64 db, {y, %131};\n"
    "wgmma.mma_async.sync.aligned.m64n256k16.f32.bf16.bf16 " WGD ", da, db, q, 1, 1, 0, 1;\n"
    "add.s32 x, %128, 4;\nadd.s32 y, %129, 256;\nmov.b64 da, {x, %131};\nmov.b64 db, {y, %131};\n"
    "wgmma.mma_async.sync.aligned.m64n256k16.f32.bf16.bf16 " WGD ", da, db, q, 1, 1, 0, 1;\n"
    "add.s32 x, %128, 6;\nadd.s32 y, %129, 384;\nmov.b64 da, {x, %131};\nmov.b64 db, {y, %131};\n"
    "wgmma.mma_async.sync.aligned.m64n256k16.f32.bf16.bf16 " WGD ", da, db, q, 1, 1, 0, 1;\n"
    "}\n"
    : "+f"(d[0]), "+f"(d[1]), "+f"(d[2]), "+f"(d[3]), "+f"(d[4]), "+f"(d[5]), "+f"(d[6]), "+f"(d[7]),
      "+f"(d[8]), "+f"(d[9]), "+f"(d[10]), "+f"(d[11]), "+f"(d[12]), "+f"(d[13]), "+f"(d[14]), "+f"(d[15]),
      "+f"(d[16]), "+f"(d[17]), "+f"(d[18]), "+f"(d[19]), "+f"(d[20]), "+f"(d[21]), "+f"(d[22]), "+f"(d[23]),
      "+f"(d[24]), "+f"(d[25]), "+f"(d[26]), "+f"(d[27]), "+f"(d[28]), "+f"(d[29]), "+f"(d[30]), "+f"(d[31]),
      "+f"(d[32]), "+f"(d[33]), "+f"(d[34]), "+f"(d[35]), "+f"(d[36]), "+f"(d[37]), "+f"(d[38]), "+f"(d[39]),
      "+f"(d[40]), "+f"(d[41]), "+f"(d[42]), "+f"(d[43]), "+f"(d[44]), "+f"(d[45]), "+f"(d[46]), "+f"(d[47]),
      "+f"(d[48]), "+f"(d[49]), "+f"(d[50]), "+f"(d[51]), "+f"(d[52]), "+f"(d[53]), "+f"(d[54]), "+f"(d[55]),
      "+f"(d[56]), "+f"(d[57]), "+f"(d[58]), "+f"(d[59]), "+f"(d[60]), "+f"(d[61]), "+f"(d[62]), "+f"(d[63]),
      "+f"(d[64]), "+f"(d[65]), "+f"(d[66]), "+f"(d[67]), "+f"(d[68]), "+f"(d[69]), "+f"(d[70]), "+f"(d[71]),
      "+f"(d[72]), "+f"(d[73]), "+f"(d[74]), "+f"(d[75]), "+f"(d[76]), "+f"(d[77]), "+f"(d[78]), "+f"(d[79]),
      "+f"(d[80]), "+f"(d[81]), "+f"(d[82]), "+f"(d[83]), "+f"(d[84]), "+f"(d[85]), "+f"(d[86]), "+f"(d[87]),
      "+f"(d[88]), "+f"(d[89]), "+f"(d[90]), "+f"(d[91]), "+f"(d[92]), "+f"(d[93]), "+f"(d[94]), "+f"(d[95]),
      "+f"(d[96]), "+f"(d[97]), "+f"(d[98]), "+f"(d[99]), "+f"(d[100]), "+f"(d[101]), "+f"(d[102]), "+f"(d[103]),
      "+f"(d[104]), "+f"(d[105]), "+f"(d[106]), "+f"(d[107]), "+f"(d[108]), "+f"(d[109]), "+f"(d[110]), "+f"(d[111]),
      "+f"(d[112]), "+f"(d[113]), "+f"(d[114]), "+f"(d[115]), "+f"(d[116]), "+f"(d[117]), "+f"(d[118]), "+f"(d[119]),
      "+f"(d[120]), "+f"(d[121]), "+f"(d[122]), "+f"(d[123]), "+f"(d[124]), "+f"(d[125]), "+f"(d[126]), "+f"(d[127])
    : "r"(a), "r"(b), "n"(FIRST), "r"(0x40000040));
#undef WGD
}

template <int FIRST> __device__ __forceinline__ void wgmma4(float (&d)[64], const uint32_t* a, uint32_t b) {
#define WGD "{%0, %1, %2, %3, %4, %5, %6, %7, %8, %9, %10, %11, %12, %13, %14, %15, %16, %17, %18, %19, %20, %21, %22, %23, %24, %25, %26, %27, %28, %29, %30, %31, %32, %33, %34, %35, %36, %37, %38, %39, %40, %41, %42, %43, %44, %45, %46, %47, %48, %49, %50, %51, %52, %53, %54, %55, %56, %57, %58, %59, %60, %61, %62, %63}"
  asm volatile("{\n.reg .pred p, q;\n.reg .b64 db;\n.reg .b32 y;\nsetp.eq.b32 p, %81, 0;\nsetp.eq.b32 q, 0, 0;\n"
    "add.s32 y, %80, 0;\nmov.b64 db, {y, %82};\n"
    "wgmma.mma_async.sync.aligned.m64n128k16.f32.bf16.bf16 " WGD ", {%64, %65, %66, %67}, db, p, 1, 1, 1;\n"
    "add.s32 y, %80, 128;\nmov.b64 db, {y, %82};\n"
    "wgmma.mma_async.sync.aligned.m64n128k16.f32.bf16.bf16 " WGD ", {%68, %69, %70, %71}, db, q, 1, 1, 1;\n"
    "add.s32 y, %80, 256;\nmov.b64 db, {y, %82};\n"
    "wgmma.mma_async.sync.aligned.m64n128k16.f32.bf16.bf16 " WGD ", {%72, %73, %74, %75}, db, q, 1, 1, 1;\n"
    "add.s32 y, %80, 384;\nmov.b64 db, {y, %82};\n"
    "wgmma.mma_async.sync.aligned.m64n128k16.f32.bf16.bf16 " WGD ", {%76, %77, %78, %79}, db, q, 1, 1, 1;\n"
    "}\n"
    : "+f"(d[0]), "+f"(d[1]), "+f"(d[2]), "+f"(d[3]), "+f"(d[4]), "+f"(d[5]), "+f"(d[6]), "+f"(d[7]),
      "+f"(d[8]), "+f"(d[9]), "+f"(d[10]), "+f"(d[11]), "+f"(d[12]), "+f"(d[13]), "+f"(d[14]), "+f"(d[15]),
      "+f"(d[16]), "+f"(d[17]), "+f"(d[18]), "+f"(d[19]), "+f"(d[20]), "+f"(d[21]), "+f"(d[22]), "+f"(d[23]),
      "+f"(d[24]), "+f"(d[25]), "+f"(d[26]), "+f"(d[27]), "+f"(d[28]), "+f"(d[29]), "+f"(d[30]), "+f"(d[31]),
      "+f"(d[32]), "+f"(d[33]), "+f"(d[34]), "+f"(d[35]), "+f"(d[36]), "+f"(d[37]), "+f"(d[38]), "+f"(d[39]),
      "+f"(d[40]), "+f"(d[41]), "+f"(d[42]), "+f"(d[43]), "+f"(d[44]), "+f"(d[45]), "+f"(d[46]), "+f"(d[47]),
      "+f"(d[48]), "+f"(d[49]), "+f"(d[50]), "+f"(d[51]), "+f"(d[52]), "+f"(d[53]), "+f"(d[54]), "+f"(d[55]),
      "+f"(d[56]), "+f"(d[57]), "+f"(d[58]), "+f"(d[59]), "+f"(d[60]), "+f"(d[61]), "+f"(d[62]), "+f"(d[63])
    : "r"(a[0]), "r"(a[1]), "r"(a[2]), "r"(a[3]), "r"(a[4]), "r"(a[5]), "r"(a[6]), "r"(a[7]), "r"(a[8]), "r"(a[9]), "r"(a[10]), "r"(a[11]), "r"(a[12]), "r"(a[13]), "r"(a[14]), "r"(a[15]),
      "r"(b), "n"(FIRST), "r"(0x40000040));
#undef WGD
}

template <int FIRST> __device__ __forceinline__ void wgmma4(float (&d)[128], const uint32_t* a, uint32_t b) {
#define WGD "{%0, %1, %2, %3, %4, %5, %6, %7, %8, %9, %10, %11, %12, %13, %14, %15, %16, %17, %18, %19, %20, %21, %22, %23, %24, %25, %26, %27, %28, %29, %30, %31, %32, %33, %34, %35, %36, %37, %38, %39, %40, %41, %42, %43, %44, %45, %46, %47, %48, %49, %50, %51, %52, %53, %54, %55, %56, %57, %58, %59, %60, %61, %62, %63, %64, %65, %66, %67, %68, %69, %70, %71, %72, %73, %74, %75, %76, %77, %78, %79, %80, %81, %82, %83, %84, %85, %86, %87, %88, %89, %90, %91, %92, %93, %94, %95, %96, %97, %98, %99, %100, %101, %102, %103, %104, %105, %106, %107, %108, %109, %110, %111, %112, %113, %114, %115, %116, %117, %118, %119, %120, %121, %122, %123, %124, %125, %126, %127}"
  asm volatile("{\n.reg .pred p, q;\n.reg .b64 db;\n.reg .b32 y;\nsetp.eq.b32 p, %145, 0;\nsetp.eq.b32 q, 0, 0;\n"
    "add.s32 y, %144, 0;\nmov.b64 db, {y, %146};\n"
    "wgmma.mma_async.sync.aligned.m64n256k16.f32.bf16.bf16 " WGD ", {%128, %129, %130, %131}, db, p, 1, 1, 1;\n"
    "add.s32 y, %144, 128;\nmov.b64 db, {y, %146};\n"
    "wgmma.mma_async.sync.aligned.m64n256k16.f32.bf16.bf16 " WGD ", {%132, %133, %134, %135}, db, q, 1, 1, 1;\n"
    "add.s32 y, %144, 256;\nmov.b64 db, {y, %146};\n"
    "wgmma.mma_async.sync.aligned.m64n256k16.f32.bf16.bf16 " WGD ", {%136, %137, %138, %139}, db, q, 1, 1, 1;\n"
    "add.s32 y, %144, 384;\nmov.b64 db, {y, %146};\n"
    "wgmma.mma_async.sync.aligned.m64n256k16.f32.bf16.bf16 " WGD ", {%140, %141, %142, %143}, db, q, 1, 1, 1;\n"
    "}\n"
    : "+f"(d[0]), "+f"(d[1]), "+f"(d[2]), "+f"(d[3]), "+f"(d[4]), "+f"(d[5]), "+f"(d[6]), "+f"(d[7]),
      "+f"(d[8]), "+f"(d[9]), "+f"(d[10]), "+f"(d[11]), "+f"(d[12]), "+f"(d[13]), "+f"(d[14]), "+f"(d[15]),
      "+f"(d[16]), "+f"(d[17]), "+f"(d[18]), "+f"(d[19]), "+f"(d[20]), "+f"(d[21]), "+f"(d[22]), "+f"(d[23]),
      "+f"(d[24]), "+f"(d[25]), "+f"(d[26]), "+f"(d[27]), "+f"(d[28]), "+f"(d[29]), "+f"(d[30]), "+f"(d[31]),
      "+f"(d[32]), "+f"(d[33]), "+f"(d[34]), "+f"(d[35]), "+f"(d[36]), "+f"(d[37]), "+f"(d[38]), "+f"(d[39]),
      "+f"(d[40]), "+f"(d[41]), "+f"(d[42]), "+f"(d[43]), "+f"(d[44]), "+f"(d[45]), "+f"(d[46]), "+f"(d[47]),
      "+f"(d[48]), "+f"(d[49]), "+f"(d[50]), "+f"(d[51]), "+f"(d[52]), "+f"(d[53]), "+f"(d[54]), "+f"(d[55]),
      "+f"(d[56]), "+f"(d[57]), "+f"(d[58]), "+f"(d[59]), "+f"(d[60]), "+f"(d[61]), "+f"(d[62]), "+f"(d[63]),
      "+f"(d[64]), "+f"(d[65]), "+f"(d[66]), "+f"(d[67]), "+f"(d[68]), "+f"(d[69]), "+f"(d[70]), "+f"(d[71]),
      "+f"(d[72]), "+f"(d[73]), "+f"(d[74]), "+f"(d[75]), "+f"(d[76]), "+f"(d[77]), "+f"(d[78]), "+f"(d[79]),
      "+f"(d[80]), "+f"(d[81]), "+f"(d[82]), "+f"(d[83]), "+f"(d[84]), "+f"(d[85]), "+f"(d[86]), "+f"(d[87]),
      "+f"(d[88]), "+f"(d[89]), "+f"(d[90]), "+f"(d[91]), "+f"(d[92]), "+f"(d[93]), "+f"(d[94]), "+f"(d[95]),
      "+f"(d[96]), "+f"(d[97]), "+f"(d[98]), "+f"(d[99]), "+f"(d[100]), "+f"(d[101]), "+f"(d[102]), "+f"(d[103]),
      "+f"(d[104]), "+f"(d[105]), "+f"(d[106]), "+f"(d[107]), "+f"(d[108]), "+f"(d[109]), "+f"(d[110]), "+f"(d[111]),
      "+f"(d[112]), "+f"(d[113]), "+f"(d[114]), "+f"(d[115]), "+f"(d[116]), "+f"(d[117]), "+f"(d[118]), "+f"(d[119]),
      "+f"(d[120]), "+f"(d[121]), "+f"(d[122]), "+f"(d[123]), "+f"(d[124]), "+f"(d[125]), "+f"(d[126]), "+f"(d[127])
    : "r"(a[0]), "r"(a[1]), "r"(a[2]), "r"(a[3]), "r"(a[4]), "r"(a[5]), "r"(a[6]), "r"(a[7]), "r"(a[8]), "r"(a[9]), "r"(a[10]), "r"(a[11]), "r"(a[12]), "r"(a[13]), "r"(a[14]), "r"(a[15]),
      "r"(b), "n"(FIRST), "r"(0x40000040));
#undef WGD
}

#define XSH 1
#define XS3 0
#define MV0 0
#define STAG 1
#define PREU 0
#define XRA 2
#define XR 37
#define NSL 100
#define NB0 1
#define NA0 1
#define GS 55
#define HFS 1
#define G0 10
#define MPF 55
#define PACEH 1
#define PACE4 6
#define PACE3 2
#define PACE 2
#define ROT3 8
#define M5 15
#define SH4 1
#define SH3 1
#define SH0 1
#define PK0 3
#define AUX_GATE 3
#define XST 8
typedef __nv_bfloat16 bf16;
constexpr int S_ = 2048, D_ = 1024, F_ = 3584;
constexpr int OFF_SPARE = 160 * 1024, OFF_STG = 192 * 1024, OFF_CS = 224 * 1024, OFF_ST = OFF_CS + 1792, OFF_BAR = OFF_ST + 1024;
constexpr int SMEM_BYTES = 232448;
constexpr uint32_t SMEM_BASE = 1024;
enum { B_FULL = 0, B_EMPTY = 8, B_SFULL = 16, B_SFA = 18, B_HALO = 20, B_RDY0 = 22, B_RDY1 = 23, B_SEMPTY = 24, B_AUX = 26, B_NUM = 28, B_PEEK = 28 };
enum { F_O = 0, F_H = 64, F_H1 = 128, F_NUM = 192 };

struct Params {
  CUtensorMap mX, mWkv, mWq, mCq, mC1, mWo, mW1a, mW1b, mW2, mO, mH, mH1, mOut;
  const bf16* x;
};

__device__ __align__(1024) bf16 g_o[S_ * D_];
__device__ __align__(1024) bf16 g_h[S_ * D_];
__device__ __align__(1024) bf16 g_h1[S_ * F_];
__device__ __align__(128) float2 g_xst[2 * S_];
__device__ __align__(128) float2 g_hst[S_ * 8];
__device__ __align__(128) float g_cs[8 * 8 * 832];
__device__ __align__(128) uint4 g_halo[16 * 8 * 2 * 256];
__device__ __align__(128) uint32_t g_hflag[256 * HFS];
__device__ __align__(128) uint32_t g_flag[F_NUM * 8];
__device__ uint32_t g_ctr;
#define PROF(idx) do {} while (0)

constexpr int SPIN_LIMIT = 1 << 22;

__device__ __forceinline__ void mbar_init(uint32_t bar, uint32_t cnt) { asm volatile("mbarrier.init.shared::cta.b64 [%0], %1;" ::"r"(bar), "r"(cnt)); }
__device__ __forceinline__ void mbar_expect_tx(uint32_t bar, uint32_t bytes) { asm volatile("mbarrier.arrive.expect_tx.shared::cta.b64 _, [%0], %1;" ::"r"(bar), "r"(bytes) : "memory"); }
__device__ __forceinline__ void mbar_arrive(uint32_t bar) { asm volatile("mbarrier.arrive.shared::cta.b64 _, [%0];" ::"r"(bar) : "memory"); }
__device__ __forceinline__ void mbar_arrive_cl(uint32_t bar_cluster_addr) { asm volatile("mbarrier.arrive.shared::cluster.b64 _, [%0];" ::"r"(bar_cluster_addr) : "memory"); }
__device__ __forceinline__ uint32_t mapa(uint32_t a, uint32_t cta) { uint32_t r; asm("mapa.shared::cluster.u32 %0, %1, %2;" : "=r"(r) : "r"(a), "r"(cta)); return r; }
__device__ __forceinline__ void spin_check(int& it) { asm volatile("{\n.reg .pred p;\nsetp.gt.s32 p, %0, %1;\n@p trap;\n}\n" ::"r"(++it), "n"(SPIN_LIMIT)); }
__device__ __forceinline__ void mbar_wait(uint32_t bar, uint32_t parity) {
  asm volatile("{\n.reg .pred p;\n.reg .s32 n;\nmov.s32 n, 0;\n"
               "W: mbarrier.try_wait.parity.shared::cta.b64 p, [%0], %1;\n@p bra D;\n"
               "add.s32 n, n, 1;\nsetp.lt.s32 p, n, %2;\n@p bra W;\ntrap;\nD:\n}\n" ::"r"(bar), "r"(parity), "n"(SPIN_LIMIT) : "memory");
}
__device__ __forceinline__ void mbar_wait_u(uint32_t bar, uint32_t parity, int& n) {
  asm volatile("{\n.reg .pred p;\n"
               "W: mbarrier.try_wait.parity.shared::cta.b64 p, [%1], %2;\n@!p add.s32 %0, %0, 1;\n"
               "setp.lt.and.s32 p, %0, %3, !p;\n@p bra.uni W;\n}\n" : "+r"(n) : "r"(bar), "r"(parity), "n"(SPIN_LIMIT) : "memory");
}
__device__ __forceinline__ void flag_add(int f) {
  asm volatile("red.relaxed.gpu.global.add.u32 [%0], 1;" ::"l"(g_flag + f * 8) : "memory");
}
__device__ __forceinline__ void flag_wait(int f, uint32_t target) {
  uint32_t v; int it = 0;
  do {
    asm volatile("ld.acquire.gpu.global.u32 %0, [%1];" : "=r"(v) : "l"(g_flag + f * 8) : "memory");
    spin_check(it);
  } while ((int)(v - target) < 0);
}
__device__ __forceinline__ void flag_peek(uint32_t dst, int f) {
  asm volatile("cp.async.cg.shared.global [%0], [%1], 16;\ncp.async.commit_group;" ::"r"(dst), "l"(g_flag + f * 8) : "memory");
}
__device__ __forceinline__ bool flag_seen(uint32_t src, uint32_t ep1) {
  uint32_t v;
  asm volatile("cp.async.wait_group 0;\nld.shared.u32 %0, [%1];" : "=r"(v) : "r"(src) : "memory");
  return (int)(v - 8 * ep1) >= 0;
}
__device__ __forceinline__ void fence_async_global() { asm volatile("fence.proxy.async.global;" ::: "memory"); }
__device__ __forceinline__ void fence_async_smem() { asm volatile("fence.proxy.async.shared::cta;" ::: "memory"); }
__device__ __forceinline__ void tma2d(uint32_t dst, const CUtensorMap* m, uint32_t bar, int c0, int c1) {
  asm volatile("cp.async.bulk.tensor.2d.shared::cluster.global.mbarrier::complete_tx::bytes [%0], [%1, {%3, %4}], [%2];"
               ::"r"(dst), "l"(m), "r"(bar), "r"(c0), "r"(c1) : "memory");
}
__device__ __forceinline__ void bulk_s2s(uint32_t dst_cl, uint32_t src, uint32_t bytes, uint32_t bar_cl) {
  asm volatile("cp.async.bulk.shared::cluster.shared::cta.mbarrier::complete_tx::bytes [%0], [%1], %2, [%3];" ::"r"(dst_cl), "r"(src), "r"(bytes), "r"(bar_cl) : "memory");
}
__device__ __forceinline__ void map_prefetch(const CUtensorMap* m) { asm volatile("prefetch.tensormap [%0];" ::"l"(m) : "memory"); }
__device__ __forceinline__ void tma2d_mc(uint32_t dst, const CUtensorMap* m, uint32_t bar, int c0, int c1, uint16_t mask = 3) {
  asm volatile("cp.async.bulk.tensor.2d.shared::cluster.global.mbarrier::complete_tx::bytes.multicast::cluster [%0], [%1, {%3, %4}], [%2], %5;"
               ::"r"(dst), "l"(m), "r"(bar), "r"(c0), "r"(c1), "h"(mask) : "memory");
}
__device__ __forceinline__ void tma3d(uint32_t dst, const CUtensorMap* m, uint32_t bar, int c0, int c1, int c2) {
  asm volatile("cp.async.bulk.tensor.3d.shared::cluster.global.mbarrier::complete_tx::bytes [%0], [%1, {%3, %4, %5}], [%2];"
               ::"r"(dst), "l"(m), "r"(bar), "r"(c0), "r"(c1), "r"(c2) : "memory");
}
__device__ __forceinline__ void tma4d(uint32_t dst, const CUtensorMap* m, uint32_t bar, int c0, int c1, int c2, int c3) {
  asm volatile("cp.async.bulk.tensor.4d.shared::cluster.global.mbarrier::complete_tx::bytes [%0], [%1, {%3, %4, %5, %6}], [%2];"
               ::"r"(dst), "l"(m), "r"(bar), "r"(c0), "r"(c1), "r"(c2), "r"(c3) : "memory");
}
__device__ __forceinline__ void tma3d_mc(uint32_t dst, const CUtensorMap* m, uint32_t bar, int c0, int c1, int c2) {
  asm volatile("cp.async.bulk.tensor.3d.shared::cluster.global.mbarrier::complete_tx::bytes.multicast::cluster [%0], [%1, {%3, %4, %5}], [%2], %6;"
               ::"r"(dst), "l"(m), "r"(bar), "r"(c0), "r"(c1), "r"(c2), "h"((uint16_t)3) : "memory");
}
__device__ __forceinline__ void tma2d_st(const CUtensorMap* m, uint32_t src, int c0, int c1) {
  asm volatile("cp.async.bulk.tensor.2d.global.shared::cta.bulk_group [%0, {%2, %3}], [%1];" ::"l"(m), "r"(src), "r"(c0), "r"(c1) : "memory");
}
__device__ __forceinline__ void tma3d_st(const CUtensorMap* m, uint32_t src, int c0, int c1, int c2) {
  asm volatile("cp.async.bulk.tensor.3d.global.shared::cta.bulk_group [%0, {%2, %3, %4}], [%1];" ::"l"(m), "r"(src), "r"(c0), "r"(c1), "r"(c2) : "memory");
}
__device__ __forceinline__ void bulk_commit() { asm volatile("cp.async.bulk.commit_group;" ::: "memory"); }
__device__ __forceinline__ void bulk_wait_read() { asm volatile("cp.async.bulk.wait_group.read 0;" ::: "memory"); }
__device__ __forceinline__ void bulk_wait_all() { asm volatile("cp.async.bulk.wait_group 0;" ::: "memory"); }
__device__ __forceinline__ void wg_fence() { asm volatile("wgmma.fence.sync.aligned;" ::: "memory"); }
__device__ __forceinline__ void wg_commit() { asm volatile("wgmma.commit_group.sync.aligned;" ::: "memory"); }
template <int N> __device__ __forceinline__ void wg_wait() { asm volatile("wgmma.wait_group.sync.aligned %0;" ::"n"(N) : "memory"); }
template <int N> __device__ __forceinline__ void reg_fence(float (&a)[N]) {
#pragma unroll
  for (int i = 0; i < N; i++) asm volatile("" : "+f"(a[i])::"memory");
}
__device__ __forceinline__ void named_sync(int id, int n) { asm volatile("bar.sync %0, %1;" ::"r"(id), "r"(n) : "memory"); }
__device__ __forceinline__ uint32_t pack2(float lo, float hi) { uint32_t r; asm("cvt.rn.bf16x2.f32 %0, %1, %2;" : "=r"(r) : "f"(hi), "f"(lo)); return r; }
__device__ __forceinline__ uint32_t pack2_relu(float lo, float hi) { uint32_t r; asm("cvt.rn.relu.bf16x2.f32 %0, %1, %2;" : "=r"(r) : "f"(hi), "f"(lo)); return r; }
__device__ __forceinline__ float ex2(float x) { float r; asm("ex2.approx.ftz.f32 %0, %1;" : "=f"(r) : "f"(x)); return r; }
__device__ __forceinline__ float rcp(float x) { float r; asm("rcp.approx.ftz.f32 %0, %1;" : "=f"(r) : "f"(x)); return r; }
__device__ __forceinline__ float bf_lo(uint32_t v) { return __uint_as_float(v << 16); }
__device__ __forceinline__ float bf_hi(uint32_t v) { return __uint_as_float(v & 0xFFFF0000u); }
__device__ __forceinline__ uint4 ldcg128(const void* p) { uint4 v; asm volatile("ld.global.cg.v4.b32 {%0, %1, %2, %3}, [%4];" : "=r"(v.x), "=r"(v.y), "=r"(v.z), "=r"(v.w) : "l"(p)); return v; }
__device__ __forceinline__ void stsm4(uint32_t a, uint32_t r0, uint32_t r1, uint32_t r2, uint32_t r3) {
  asm volatile("stmatrix.sync.aligned.m8n8.x4.shared.b16 [%0], {%1, %2, %3, %4};" ::"r"(a), "r"(r0), "r"(r1), "r"(r2), "r"(r3) : "memory");
}
__device__ __forceinline__ void ldsm4(uint32_t a, uint32_t& r0, uint32_t& r1, uint32_t& r2, uint32_t& r3) {
  asm volatile("ldmatrix.sync.aligned.m8n8.x4.shared.b16 {%0, %1, %2, %3}, [%4];" : "=r"(r0), "=r"(r1), "=r"(r2), "=r"(r3) : "r"(a) : "memory");
}
__device__ __forceinline__ uint32_t movm(uint32_t a) { uint32_t d; asm volatile("movmatrix.sync.aligned.m8n8.trans.b16 %0, %1;" : "=r"(d) : "r"(a)); return d; }
__device__ __forceinline__ void mma16(float (&c)[4], uint32_t a0, uint32_t a1, uint32_t a2, uint32_t a3, uint32_t b0, uint32_t b1) {
  asm volatile("mma.sync.aligned.m16n8k16.row.col.f32.bf16.bf16.f32 {%0,%1,%2,%3}, {%4,%5,%6,%7}, {%8,%9}, {%0,%1,%2,%3};"
               : "+f"(c[0]), "+f"(c[1]), "+f"(c[2]), "+f"(c[3]) : "r"(a0), "r"(a1), "r"(a2), "r"(a3), "r"(b0), "r"(b1));
}
__device__ __forceinline__ void mma8(float (&c)[4], uint32_t a0, uint32_t a1, uint32_t b0) {
  asm volatile("mma.sync.aligned.m16n8k8.row.col.f32.bf16.bf16.f32 {%0,%1,%2,%3}, {%4,%5}, {%6}, {%0,%1,%2,%3};"
               : "+f"(c[0]), "+f"(c[1]), "+f"(c[2]), "+f"(c[3]) : "r"(a0), "r"(a1), "r"(b0));
}
__device__ __forceinline__ float2 lds64f(uint32_t a) { float2 v; asm volatile("ld.shared.v2.f32 {%0, %1}, [%2];" : "=f"(v.x), "=f"(v.y) : "r"(a)); return v; }
__device__ __forceinline__ uint4 lds128(uint32_t a) { uint4 v; asm volatile("ld.shared.v4.b32 {%0, %1, %2, %3}, [%4];" : "=r"(v.x), "=r"(v.y), "=r"(v.z), "=r"(v.w) : "r"(a)); return v; }
__device__ __forceinline__ void sts128(uint32_t a, uint32_t x, uint32_t y, uint32_t z, uint32_t w) { asm volatile("st.shared.v4.b32 [%0], {%1, %2, %3, %4};" ::"r"(a), "r"(x), "r"(y), "r"(z), "r"(w) : "memory"); }
__device__ __forceinline__ void sts64f(uint32_t a, float x, float y) { asm volatile("st.shared.v2.f32 [%0], {%1, %2};" ::"r"(a), "f"(x), "f"(y) : "memory"); }
__device__ __forceinline__ float4 lds128f(uint32_t a) { float4 v; asm volatile("ld.shared.v4.f32 {%0, %1, %2, %3}, [%4];" : "=f"(v.x), "=f"(v.y), "=f"(v.z), "=f"(v.w) : "r"(a)); return v; }
__device__ __forceinline__ void st_tag2(void* p, float x, float y, uint32_t tag) {
  asm volatile("st.relaxed.gpu.global.v2.b32 [%0], {%1, %2};" ::"l"(p), "r"((__float_as_uint(x) & ~3u) | tag), "r"((__float_as_uint(y) & ~3u) | tag) : "memory");
}
__device__ __forceinline__ float4 ld_tag4(const void* p) { float4 v; asm volatile("ld.relaxed.gpu.global.v4.f32 {%0, %1, %2, %3}, [%4];" : "=f"(v.x), "=f"(v.y), "=f"(v.z), "=f"(v.w) : "l"(p) : "memory"); return v; }
__device__ __forceinline__ uint32_t tag_bad(const float4& v, uint32_t tag) {
  return ((__float_as_uint(v.x) ^ tag) | (__float_as_uint(v.y) ^ tag) | (__float_as_uint(v.z) ^ tag) | (__float_as_uint(v.w) ^ tag)) & 3u;
}

template <int F> __device__ __forceinline__ void wgmma4(float (&d)[64], uint32_t a, uint32_t b) { wgmma4_n128<F>(d, a, b); }
template <int F> __device__ __forceinline__ void wgmma4(float (&d)[96], uint32_t a, uint32_t b) { wgmma4_n192<F>(d, a, b); }
template <int F> __device__ __forceinline__ void wgmma4(float (&d)[128], uint32_t a, uint32_t b) { wgmma4_n256<F>(d, a, b); }

struct Ctx { uint32_t sb, bar, ep1; int i, j, rank; };
template <int PH> struct Geo {
  static constexpr int N0 = PH * 16;
  static constexpr int NS = PH == 5 ? 56 : 16;
  static constexpr int NCH = (PH == 0 || PH == 3) ? 4 : (PH == 4 ? 3 : 2);
  static constexpr int SB = 16384 + NCH * 8192;
  static constexpr int DEPTH = NCH == 2 ? 6 : 4;
  static constexpr int SLOT0 = PH == 0 ? 1 : PH == 1 ? 2 : PH == 3 ? 3 : 0;
  static __device__ __forceinline__ int dep(int m) {
    if (PH == 5 && m >= 5 && m <= M5) return m < M5 ? N0 + m - 5 : -1;
    if (m >= DEPTH || PH == 0 || PH == 2) return N0 + m - DEPTH;
    if (PH == 1) return m == 0 ? 12 : 13 + (m >> 1);
    if (PH == 3) return m == 0 ? N0 - 5 : N0 - 4 + m;
    if (PH == 4) return N0 - 3 + (m < 2 ? m : 2);
    return N0 - 4 + (m < 3 ? m : 3);
  }
  static __device__ __forceinline__ int next(int slot, int m) { return slot + 1 == (PH == 5 && m < M5 - 5 ? 5 : DEPTH) ? 0 : slot + 1; }
  static __device__ __forceinline__ int slot_of(int m) { return PH == 5 ? (m >= M5 - 5 ? (m - M5 + 5) % 6 : m % 5) : (SLOT0 + m) % DEPTH; }
  static __device__ __forceinline__ bool own(int m) { return (PH == 2 || PH == 3) && m < 2; }
  static __device__ __forceinline__ bool local(int m) { return (PH == 2 || PH == 3) && m < 4; }
  static __device__ __forceinline__ int koff(int m, int j) {
    if (local(m)) return (128 * j) ^ (64 * m);
    if (PH == 2 || PH == 3) { const int t = m < 10 ? m - 4 : m - 10; return 128 * (t < (j & 6) ? t : t + 2) + (m < 10 ? 0 : 64); }
    if (PH == 5) return m < 32 ? 448 * (m >> 2) + 64 * (m & 3) : 448 * ((m - 32) / 3) + 256 + 64 * ((m - 32) % 3);
    return 64 * m;
  }
};
__device__ __forceinline__ void wait_empty(const Ctx& c, int d) { mbar_wait(c.bar + 8 * (B_EMPTY + (d & 7)), (d >> 3) & 1); }

__device__ __forceinline__ void set_progress(const Ctx& c, int d) { asm volatile("st.volatile.shared.s32 [%0], %1;" ::"r"(c.bar + 8 * B_PEEK + 16), "r"(d) : "memory"); }
__device__ __forceinline__ void wait_progress(const Ctx& c, int d) {
  asm volatile("{\n.reg .pred p;\n.reg .s32 n, v;\nmov.s32 n, 0;\n"
               "W: ld.volatile.shared.s32 v, [%0];\nsetp.ge.s32 p, v, %1;\n@p bra D;\nnanosleep.u32 %3;\n"
               "add.s32 n, n, 1;\nsetp.lt.s32 p, n, %2;\n@p bra W;\ntrap;\nD:\n}\n" ::"r"(c.bar + 8 * B_PEEK + 16), "r"(d), "n"(SPIN_LIMIT), "n"(NSL) : "memory");
}
static_assert(PACE4 + PACE <= M5 - 6, "the first h1 stores must not wait for slot 5");

template <int PH> __device__ __forceinline__ void produce_b(const Params& p, const Ctx& c, int m0, int m1) {
  using G = Geo<PH>;
  int slot = G::slot_of(m0);
#pragma unroll 1
  for (int m = m0; m < m1; m++) {
    const int n = G::N0 + m, d = G::dep(m);
    if (d >= 0) wait_empty(c, d);
    if (PH == 5 && m == M5) { mbar_wait(c.bar + 8 * B_SEMPTY, 1); mbar_wait(c.bar + 8 * (B_SEMPTY + 1), 1); }
    const uint32_t fb = c.bar + 8 * (n & 7), dst = c.sb + slot * G::SB + 16384;
    mbar_expect_tx(fb, G::own(m) ? G::SB - 16384 : G::SB);
    const int k0 = G::koff(m, c.j);
    if (PH == 0 && m < NA0) { tma3d(dst - 16384, &p.mX, fb, k0, 0, 64 * c.i); tma3d(dst - 8192, &p.mX, fb, k0, 1, 64 * c.i); }
    if (PH == 0) tma4d(dst, &p.mWkv, fb, 0, k0, 2 * c.j, 1);
    if (PH == 1) tma3d(dst, &p.mWq, fb, 0, k0, 2 * c.j);
    if (PH == 2) tma3d(dst, &p.mWo, fb, 0, k0, 2 * c.j);
    if (PH == 3) tma3d(dst, &p.mW1a, fb, 0, k0, 7 * c.j);
    if (PH == 4) tma3d(dst, &p.mW1b, fb, 0, k0, 7 * c.j + 4);
    if (PH == 5) tma3d(dst, &p.mW2, fb, 0, k0, 2 * c.j);
    if (d >= 0) set_progress(c, d);
    if (PH == 0 && m == 0) PROF(2);
    if (PH == 5 && m == MPF) map_prefetch(&p.mOut);
    slot = G::next(slot, m);
  }
}
template <int PH> __device__ __forceinline__ void produce_a(const Params& p, const Ctx& c, bool& seen) {
  using G = Geo<PH>;
  constexpr int M1 = PH == 5 ? 32 : PH == 4 ? 16 : 10;
  const int F0 = (PH == 2 ? F_O : PH == 3 ? F_H : F_H1) + c.i * 4 + c.rank;
  int slot = G::SLOT0;
  const int row = 128 * c.i + 64 * c.rank;
#pragma unroll 1
  for (int m = 0; m < G::NS; m++) {
    if (!G::local(m) && (PH > 0 || m >= NA0)) {
      const int n = G::N0 + m, d = G::dep(m);
      if (m == 4 && (PH == 2 || PH == 3)) { flag_wait(F0, 8 * c.ep1); fence_async_global(); PROF(PH == 2 ? 24 : 26); }
      if (d >= 0) wait_empty(c, d);
      if ((m == M1 && PH >= 2 && PH != 4) || (PH == 5 && m == 0)) {
        if (!seen) { if (!flag_seen(c.bar + 8 * B_PEEK, c.ep1)) flag_wait(F0 + (m ? 2 : 0), 8 * c.ep1); fence_async_global(); }
        PROF(PH == 2 ? 25 : PH == 3 ? 29 : 27 + (m >> 5));
      }
      const uint32_t fb = c.bar + 8 * (n & 7), dst = c.sb + slot * G::SB + c.rank * 8192;
      const int k0 = G::koff(m, c.j);
      if (PH <= 1) tma3d_mc(dst, &p.mX, fb, k0, c.rank, 64 * c.i);
      if (PH == 2) tma2d_mc(dst, &p.mO, fb, k0, row);
      if (PH == 3 || PH == 4) tma2d_mc(dst, &p.mH, fb, k0, row);
      if (PH == 5) tma2d_mc(dst, &p.mH1, fb, k0, row);
      if (PH == 0 && m == NA0) PROF(3);
      if (PH >= 2 && (m == M1 - PK0 || m == M1 - 1)) {
        seen = m == M1 - 1 && flag_seen(c.bar + 8 * B_PEEK, c.ep1);
        if (seen) fence_async_global(); else flag_peek(c.bar + 8 * B_PEEK, F0 + (PH == 4 ? 0 : 2));
      }
    }
    slot = G::next(slot, m);
  }
}

struct Con { uint32_t rel, stg, da; int wg, w, lane, spin; bool do_rel; };
template <int PH, bool FIRST, bool RS = false> __device__ __forceinline__ void issue(float (&acc)[Geo<PH>::NCH * 32], const Ctx& c, Con& k, int m, int slot, const uint32_t* ar = nullptr) {
  using G = Geo<PH>;
  const int n = G::N0 + m;
  mbar_wait_u(c.bar + 8 * (n & 7), (n >> 3) & 1, k.spin);
  if (m == 0 && k.do_rel) PROF(32 + 32 * k.wg + 3 * PH);
  if (PH == 2 && (m == 4 || m == 10) && k.do_rel) PROF(32 + 32 * k.wg + 19 + (m >> 3));
  if (PH == 3 && (m == 2 || m == 4) && k.do_rel) PROF(32 + 32 * k.wg + 20 + (m >> 1));
  if (PH == 2 && (m == 2 || m == 3 || m == 5) && k.do_rel) PROF(32 + 32 * k.wg + 22 + m);
  if (PH == 3 && (m == 3 || m == 10) && k.do_rel) PROF(32 + 32 * k.wg + 28 + (m >> 3));
  const uint32_t so = slot * (G::SB >> 4);
  wg_fence();
  if constexpr (RS) wgmma4<FIRST>(acc, ar, so + (((SMEM_BASE + 16384) >> 4) | (512u << 16)));
  else wgmma4<FIRST>(acc, k.da + so, so + (((SMEM_BASE + 16384) >> 4) | (512u << 16)));
  wg_commit();
}
template <int PH> __device__ __forceinline__ void retire(Con& k, int m) {
  wg_wait<1>();
  if (k.do_rel && (PH < 5 || m <= 50)) mbar_arrive_cl(k.rel + 8 * ((Geo<PH>::N0 + m - 1) & 7));
}
template <int PH, int PEND = 0> __device__ __forceinline__ void finish(Con& k) {
  wg_wait<PEND>();
  if (PH < 5 && k.do_rel) mbar_arrive_cl(k.rel + 8 * 7);
  if (k.do_rel) PROF(32 + 32 * k.wg + 3 * PH + 1);
}
template <int PH> __device__ __forceinline__ void steps(float (&acc)[Geo<PH>::NCH * 32], const Ctx& c, Con& k, int m0, int m1) {
  using G = Geo<PH>;
  int slot = G::slot_of(m0);
#pragma unroll 1
  for (int m = m0; m < m1; m++) {
    issue<PH, false>(acc, c, k, m, slot);
    retire<PH>(k, m);
    slot = G::next(slot, m);
  }
}
#define ISSUE(PH, acc, m) issue<PH, false>(acc, c, k, m, Geo<PH>::slot_of(m))
#define ISSUE_RS(PH, acc, r) issue<PH, true, true>(acc, c, k, 0, Geo<PH>::SLOT0, r); issue<PH, false, true>(acc, c, k, 1, Geo<PH>::slot_of(1), r + 16); retire<PH>(k, 1)
#define LAST(PH, acc, on) \
  if (on && k.wg) { pre_load<PH>(pr, c, k); wg_wait<0>(); if (k.do_rel) mbar_arrive_cl(k.rel + 8 * 6); named_sync(4, 256); } \
  ISSUE(PH, acc, 15); \
  if (!(on && k.wg)) { pre_load<PH>(pr, c, k); retire<PH>(k, 15); } \
  finish<PH>(k); \
  if (on && !k.wg) asm volatile("bar.arrive 4, 256;" ::: "memory")
#define ISSUE0(PH, acc) issue<PH, true>(acc, c, k, 0, Geo<PH>::SLOT0)

__device__ __forceinline__ void handoff(const Ctx& c, Con& k, int bar = B_SFULL) {
  fence_async_smem();
  __syncwarp();
  if (k.lane == 0) mbar_arrive(c.bar + 8 * (bar + k.wg));
}

struct Pre { float4 cs[4]; float2 s0, s1; };
template <int PH> __device__ __forceinline__ void pre_load(Pre& a, const Ctx& c, Con& k) {
  if (PH == 0) mbar_wait_u(c.bar + 8 * B_RDY0, 0, k.spin);
  if (PH == 1) { mbar_wait_u(c.bar + 8 * B_RDY1, 0, k.spin); mbar_wait_u(c.bar + 8 * (B_HALO + k.wg), 0, k.spin); }
  if (PH == 4) { mbar_wait_u(c.bar + 8 * B_RDY1, 1, k.spin); mbar_wait_u(c.bar + 8 * (B_SEMPTY + k.wg), 0, k.spin); }
  if (PH == 3) { mbar_wait_u(c.bar + 8 * B_RDY0, 1, k.spin); mbar_wait_u(c.bar + 8 * (B_EMPTY + 4), 1, k.spin); }
  const uint32_t sta = c.sb + OFF_ST + (k.wg * 64 + k.w * 16 + (k.lane >> 2)) * 8;
  a.s0 = lds64f(sta); a.s1 = lds64f(sta + 64);
  a.s0.x = -a.s0.x; a.s1.x = -a.s1.x;
#pragma unroll
  for (int u = 0; u < 4; u++) a.cs[u] = lds128f(c.sb + OFF_CS + (Geo<PH>::NCH == 4 ? 0 : 1024) + (PH == 3 ? u ^ ROT3 : u) * 64 + (k.lane & 3) * 16);
}
template <int PH, int U0, int U1> __device__ __forceinline__ void qkv_pack(uint32_t (&pk)[Geo<PH>::NCH * 8][2], const float (&acc)[Geo<PH>::NCH * 32], Pre& a, const Ctx& c, Con& k) {
  const uint32_t csa = c.sb + OFF_CS + PH * 1024 + (k.lane & 3) * 16;
#pragma unroll
  for (int u = U0; u < U1; u++) {
    const float4 s = a.cs[u & 3];
    if (u + 4 < Geo<PH>::NCH * 4) a.cs[u & 3] = lds128f(csa + (u + 4) * 64);
    float v[8];
#pragma unroll
    for (int e = 0; e < 8; e++) {
      v[e] = fmaf((e & 2) ? a.s1.x : a.s0.x, (e & 4) ? ((e & 1) ? s.w : s.z) : ((e & 1) ? s.y : s.x), acc[8 * u + e]);
      if (PH == 0) v[e] *= (e & 2) ? a.s1.y : a.s0.y;
    }
#pragma unroll
    for (int e = 0; e < 4; e++) pk[2 * u + (e >> 1)][e & 1] = pack2(v[2 * e], v[2 * e + 1]);
  }
}
#define HALO_SRC(kv, H, x) kv[((x) < 8 ? 0 : 8) + 8 * (H) + (x)][1]
template <int H> __device__ __forceinline__ void halo_publish(uint32_t (&kv)[32][2], const Ctx& c, Con& k) {
  const uint32_t ha = k.stg + ((k.w + 1) & 3) * 2048 + k.lane * 16 + H * 8192;
#pragma unroll
  for (int u = 0; u < 4; u++) sts128(ha + u * 512, HALO_SRC(kv, H, 4 * u), HALO_SRC(kv, H, 4 * u + 1), HALO_SRC(kv, H, 4 * u + 2), HALO_SRC(kv, H, 4 * u + 3));
  if (H == 0) return;
  if (k.w == 3) { fence_async_smem(); asm volatile("bar.arrive %0, 64;" ::"r"(5 + k.wg) : "memory"); }
  else { __syncwarp(); if (k.lane == 0) mbar_arrive(c.bar + 8 * (B_HALO + k.wg)); }
}
struct Att { uint32_t hl[16], pp[4][2], z[4]; float l[4][2], mx[4], o[8][4], dn[2][4]; };
template <int H> __device__ __forceinline__ void att_halo(Att& s, Con& k) {
#pragma unroll
  for (int u = 0; u < 4; u++) { const uint4 v = lds128(k.stg + H * 8192 + k.w * 2048 + k.lane * 16 + u * 512); s.hl[4 * u] = v.x; s.hl[4 * u + 1] = v.y; s.hl[4 * u + 2] = v.z; s.hl[4 * u + 3] = v.w; }
}
template <int H> __device__ __forceinline__ void att_qk(Att& s, const uint32_t (&q)[16][2], uint32_t (&kv)[32][2], float lmask, const Ctx& c, Con& k) {
  auto& hl = s.hl; auto& l = s.l;
  const bool g0 = 2 * (k.lane & 3) > (k.lane >> 2), g1 = 2 * (k.lane & 3) + 1 > (k.lane >> 2), nohalo = (k.w == 0 && c.i == 0);
  float sa[2][4], sb[2][4], sh[2][4];
#pragma unroll
  for (int e = 0; e < 8; e++) { sa[e >> 2][e & 3] = 0.f; sb[e >> 2][e & 3] = 0.f; sh[e >> 2][e & 3] = 0.f; }
#pragma unroll
  for (int ks = 0; ks < 2; ks++)
#pragma unroll
    for (int hd = 0; hd < 2; hd++) {
      const int x = 4 * hd + 2 * ks, t = 8 * H + x;
      mma16(sa[hd], q[t][0], q[t][1], q[t + 1][0], q[t + 1][1], kv[t][0], kv[t + 1][0]);
      mma16(sb[hd], q[t][0], q[t][1], q[t + 1][0], q[t + 1][1], kv[t][1], kv[t + 1][1]);
      mma16(sh[hd], q[t][0], q[t][1], q[t + 1][0], q[t + 1][1], hl[x], hl[x + 1]);
    }
#pragma unroll
  for (int t = 16 + 8 * H; t < 24 + 8 * H; t++) if (!MV0) kv[t][0] = movm(kv[t][0]);
#pragma unroll
  for (int hd = 0; hd < 2; hd++) {
    if (nohalo) sh[hd][0] = sh[hd][1] = lmask;
    l[2 * hd][0] = g0 ? sh[hd][0] : sa[hd][0]; l[2 * hd][1] = g1 ? sh[hd][1] : sa[hd][1];
    l[2 * hd + 1][0] = g0 ? sa[hd][2] : sb[hd][2]; l[2 * hd + 1][1] = g1 ? sa[hd][3] : sb[hd][3];
  }
}
__device__ __forceinline__ void att_soft(Att& s, float sc0, float sc1, Con& k) {
  auto& l = s.l; auto& mx = s.mx; auto& pp = s.pp; auto& z = s.z;
  const bool g0 = 2 * (k.lane & 3) > (k.lane >> 2), g1 = 2 * (k.lane & 3) + 1 > (k.lane >> 2);
#pragma unroll
  for (int e = 0; e < 4; e++) mx[e] = fmaxf(l[e][0], l[e][1]);
#pragma unroll
  for (int o = 1; o < 3; o++)
#pragma unroll
    for (int e = 0; e < 4; e++) mx[e] = fmaxf(mx[e], __shfl_xor_sync(~0u, mx[e], o));
#pragma unroll
  for (int e = 0; e < 4; e++) {
    const float sc = (e & 1) ? sc1 : sc0;
    const uint32_t pr = pack2(ex2((l[e][0] - mx[e]) * sc), ex2((l[e][1] - mx[e]) * sc)), mk = (g0 ? 0xFFFFu : 0u) | (g1 ? 0xFFFF0000u : 0u);
    pp[e][0] = pr & mk; pp[e][1] = pr & ~mk; z[e] = pr & (k.spin >> 31);
    mx[e] = __uint_as_float(pr);
  }
}
template <int H> __device__ __forceinline__ void att_pv(Att& s, const uint32_t (&kv)[32][2]) {
  auto& hl = s.hl; auto& mx = s.mx; auto& pp = s.pp; auto& z = s.z; auto& o = s.o; auto& dn = s.dn;
#pragma unroll
  for (int hd = 0; hd < 2; hd++) {
    dn[hd][0] = dn[hd][1] = dn[hd][2] = dn[hd][3] = 0.f;
    mma8(dn[hd], __float_as_uint(mx[2 * hd]), __float_as_uint(mx[2 * hd + 1]), 0x3F803F80u);
  }
#pragma unroll
  for (int t = 0; t < 8; t++) {
    o[t][0] = o[t][1] = o[t][2] = o[t][3] = 0.f;
    mma16(o[t], pp[(t >> 2) * 2][1], pp[(t >> 2) * 2 + 1][0], z[(t >> 2) * 2], pp[(t >> 2) * 2 + 1][1], kv[16 + 8 * H + t][0], kv[16 + 8 * H + t][1]);
  }
#pragma unroll
  for (int t = 0; t < 8; t++) mma8(o[t], pp[(t >> 2) * 2][0], z[(t >> 2) * 2 + 1], hl[8 + t]);
}
template <int H> __device__ __forceinline__ void att_out(Att& s, uint32_t* of, const Ctx& c, Con& k) {
  auto& o = s.o; auto& dn = s.dn;
  const uint32_t oa = k.stg + H * 8192 + (k.w * 16 + (k.lane & 15)) * 128;
#pragma unroll
  for (int u = 0; u < 4; u++) {
    const float r0 = rcp(dn[u >> 1][0]), r1 = rcp(dn[u >> 1][2]);
#pragma unroll
    for (int e = 0; e < 4; e++) of[4 * u + e] = pack2(o[2 * u + (e >> 1)][2 * (e & 1)] * ((e & 1) ? r1 : r0), o[2 * u + (e >> 1)][2 * (e & 1) + 1] * ((e & 1) ? r1 : r0));
    stsm4(oa + (((2 * u + (k.lane >> 4)) ^ (k.lane & 7)) << 4), of[4 * u], of[4 * u + 1], of[4 * u + 2], of[4 * u + 3]);
  }
  handoff(c, k, H == 0 ? B_SFA : B_SFULL);
  if (k.lane == 0) {
    const uint32_t peer = mapa(c.sb, c.rank ^ 1);
    bulk_s2s(peer + (2 + H) * 32768 + k.wg * 8192 + k.w * 2048, k.stg + H * 8192 + k.w * 2048, 2048, peer + OFF_BAR + 8 * (2 + H));
  }
}

__device__ __forceinline__ void res_load(uint32_t (&res)[32], uint32_t bar, uint32_t par, Con& k) {
  mbar_wait_u(bar, par, k.spin);
#pragma unroll
  for (int u = 0; u < 8; u++)
    ldsm4(k.stg + (u >> 2) * 8192 + (k.w * 16 + (k.lane & 15)) * 128 + ((((2 * u & 7) + (k.lane >> 4)) ^ (k.lane & 7)) << 4), res[4 * u], res[4 * u + 1], res[4 * u + 2], res[4 * u + 3]);
}
__device__ __forceinline__ void res_unpack(float (&rf)[64], const uint32_t (&res)[32]) {
#pragma unroll
  for (int x = 0; x < 32; x++) { rf[2 * x] = bf_lo(res[x]); rf[2 * x + 1] = bf_hi(res[x]); }
  if (PREU) reg_fence(rf);
}
template <int CH> __device__ __forceinline__ void epi_res(const float (&acc)[64], const float (&rf)[64], uint32_t (&res)[32], float sc0, float sc1, Con& k) {
  const uint32_t oa = k.stg + CH * 8192 + (k.w * 16 + (k.lane & 15)) * 128;
#pragma unroll
  for (int u = 0; u < 4; u++) {
#pragma unroll
    for (int e = 0; e < 4; e++) {
      const int x = 16 * CH + 4 * u + e;
      const float sc = (e & 1) ? sc1 : sc0;
      res[x] = pack2(fmaf(sc, acc[2 * x], rf[2 * x]), fmaf(sc, acc[2 * x + 1], rf[2 * x + 1]));
    }
    stsm4(oa + (((2 * u + (k.lane >> 4)) ^ (k.lane & 7)) << 4), res[16 * CH + 4 * u], res[16 * CH + 4 * u + 1], res[16 * CH + 4 * u + 2], res[16 * CH + 4 * u + 3]);
  }
}

template <int NCH, int C0, int C1> __device__ __forceinline__ void epi_ffn1(const float (&acc)[NCH * 32], Pre& a, const Ctx& c, Con& k) {
  const uint32_t csa = c.sb + OFF_CS + (NCH == 4 ? 0 : 1024) + (k.lane & 3) * 16;
  const uint32_t rowo = (k.w * 16 + (k.lane & 15)) * 128;
#pragma unroll
  for (int x = C0; x < C1; x++) {
    const int u = NCH == 4 ? x ^ ROT3 : x, ch = u >> 2, t = 8 * u;
    const uint32_t cb = ch < 2 ? k.stg + ch * 8192 : c.sb + OFF_SPARE + k.wg * 8192 + (ch == NCH - 1 ? 16384 : 0);
    const float4 s = a.cs[u & 3];
    const uint32_t v0 = pack2_relu(fmaf(a.s0.x, s.x, acc[t]), fmaf(a.s0.x, s.y, acc[t + 1])), v1 = pack2_relu(fmaf(a.s1.x, s.x, acc[t + 2]), fmaf(a.s1.x, s.y, acc[t + 3]));
    const uint32_t v2 = pack2_relu(fmaf(a.s0.x, s.z, acc[t + 4]), fmaf(a.s0.x, s.w, acc[t + 5])), v3 = pack2_relu(fmaf(a.s1.x, s.z, acc[t + 6]), fmaf(a.s1.x, s.w, acc[t + 7]));
    if (x + 4 < NCH * 4) a.cs[u & 3] = lds128f(csa + (NCH == 4 ? (x + 4) ^ ROT3 : x + 4) * 64);
    stsm4(cb + rowo + ((((2 * u & 7) + (k.lane >> 4)) ^ (k.lane & 7)) << 4), v0, v1, v2, v3);
  }
  if (C1 == 4 * NCH) handoff(c, k);
}

__device__ __forceinline__ void acc_stat(uint32_t v, float sh, float& s1, float& s2) {
  const float x = bf_lo(v) - sh, y = bf_hi(v) - sh;
  s1 += x + y; s2 = fmaf(y, y, fmaf(x, x, s2));
}
template <bool PF> __device__ __forceinline__ void unit_load(const Params& p, int j, int u, uint32_t dst, uint32_t bar) {
  const int ch = u >> 3;
  const CUtensorMap* mp = ch < 6 ? &p.mCq : &p.mC1;
  const int col = ch < 6 ? (ch < 4 ? 1024 + (ch >> 1) * 1024 : 0) + 128 * j + 64 * (ch & 1) : 448 * j + 64 * (ch - 6);
  if (PF) {
    asm volatile("cp.async.bulk.prefetch.tensor.2d.L2.global [%0, {%1, %2}];" ::"l"(mp), "r"(col), "r"((u & 7) * 128) : "memory");
  } else {
    mbar_expect_tx(bar, 16384);
    tma2d(dst, mp, bar, col, (u & 7) * 128);
  }
}
__device__ __forceinline__ void unit_sum(int j, uint32_t tag, int u, uint32_t src, int lane) {
  float s[8];
#pragma unroll
  for (int e = 0; e < 8; e++) s[e] = 0.f;
  uint4 v[2][4];
#pragma unroll
  for (int e = 0; e < 4; e++) v[0][e] = lds128(src + e * 512 + lane * 16);
#pragma unroll 1
  for (int b = 0; b < 4; b++) {
#pragma unroll
    for (int h = 0; h < 2; h++) {
#pragma unroll
      for (int e = 0; e < 4; e++) v[h ^ 1][e] = lds128(src + ((2 * b + h + 1) & 7) * 2048 + e * 512 + lane * 16);
#pragma unroll
      for (int e = 0; e < 4; e++) {
        const uint4 t = v[h][e];
        s[0] += bf_lo(t.x); s[1] += bf_hi(t.x); s[2] += bf_lo(t.y); s[3] += bf_hi(t.y);
        s[4] += bf_lo(t.z); s[5] += bf_hi(t.z); s[6] += bf_lo(t.w); s[7] += bf_hi(t.w);
      }
    }
  }
  const bool hi = lane & 16, md = lane & 8;
#pragma unroll
  for (int e = 0; e < 4; e++) s[e] = (hi ? s[e + 4] : s[e]) + __shfl_xor_sync(~0u, hi ? s[e] : s[e + 4], 16);
#pragma unroll
  for (int e = 0; e < 2; e++) s[e] = (md ? s[e + 2] : s[e]) + __shfl_xor_sync(~0u, md ? s[e] : s[e + 2], 8);
  st_tag2(g_cs + ((u & 7) * 8 + j) * 832 + (u >> 3) * 64 + (lane & 7) * 8 + (lane >> 4) * 4 + (md ? 2 : 0), s[0], s[1], tag);
}
__device__ __forceinline__ void cs_gather(const Ctx& c, int col, int dcol) {
  float4 v[8]; uint32_t bad; int it = 0;
  do {
    bad = 0;
#pragma unroll
    for (int u = 0; u < 8; u++) v[u] = ld_tag4(g_cs + (u * 8 + c.j) * 832 + col);
#pragma unroll
    for (int u = 0; u < 8; u++) bad |= tag_bad(v[u], c.ep1);
    spin_check(it);
  } while (bad);
#pragma unroll
  for (int u = 1; u < 8; u++) { v[0].x += v[u].x; v[0].y += v[u].y; v[0].z += v[u].z; v[0].w += v[u].w; }
  const uint32_t da = c.sb + OFF_CS + (dcol >> 4) * 64 + (dcol & 4) * 8 + (dcol & 8);
  sts64f(da, v[0].x, v[0].y); sts64f(da + 16, v[0].z, v[0].w);
}
__device__ __forceinline__ void aux_warp(const Params& p, const Ctx& c, int a, int lane) {
  const uint32_t spare = c.sb + OFF_SPARE, mystg = c.sb + OFF_STG + a * 16384;
  const uint32_t bA = c.bar + 8 * (B_AUX + a), bSF = c.bar + 8 * (B_SFULL + a), bSE = c.bar + 8 * (B_SEMPTY + a);
  const bool lead = (a == 0 && lane == 0);
  const int row0 = 128 * c.i + 64 * a, u0 = 2 * c.i + a;
  const uint32_t tag = c.ep1 & 3, peer = mapa(c.sb, c.rank ^ 1);
  if (lane == 0) {
    if (a == 0) {
      wait_progress(c, 0);
#pragma unroll
      for (int s = 2; s < 13; s++) map_prefetch(&p.mX + s);
    }
    wait_progress(c, AUX_GATE);
    unit_load<false>(p, c.j, u0, mystg, bA);
  }
  mbar_wait(bA, 0);
  if (lead) PROF(4);
  unit_sum(c.j, tag, u0, mystg, lane);
  if (lead) PROF(6);
  wait_progress(c, G0);
  {
    float4 v; int it = 0;
    do { v = ld_tag4(g_xst + (64 * c.i + 32 * a + lane) * 4); spin_check(it); } while (tag_bad(v, tag));
    sts64f(c.sb + OFF_ST + (32 * a + lane) * 8, v.x, v.y); sts64f(c.sb + OFF_ST + (64 + 32 * a + lane) * 8, v.z, v.w);
  }
#pragma unroll 1
  for (int r = 0; r < 4; r++) {
    if (r == 2) {
      if (lane == 0) {
        mbar_wait(c.bar + 8 * (B_SFA + a), 1);
        tma2d_st(&p.mH, mystg, 128 * c.j, row0); bulk_commit();
        if (lead) PROF(18);
        wait_empty(c, 46);
        bulk_s2s(peer + 1 * 49152 + a * 8192, mystg, 8192, peer + OFF_BAR + 8 * (50 & 7));
        bulk_wait_all(); flag_add(F_H + c.i * 4 + a);
        if (lead) PROF(19);
        mbar_wait(bSF, 1);
        wait_empty(c, 47);
        bulk_s2s(peer + 2 * 49152 + a * 8192, mystg + 8192, 8192, peer + OFF_BAR + 8 * (51 & 7));
        wait_progress(c, 48 + PACEH + a);
        tma2d_st(&p.mH, mystg + 8192, 128 * c.j + 64, row0); bulk_commit();
        bulk_wait_all(); flag_add(F_H + c.i * 4 + 2 + a);
        if (lead) PROF(20);
      }
      __syncwarp();
      if (lane == 0) mbar_arrive(bSE);
      if (lead) PROF(12);
      wait_progress(c, GS);
      {
        float4 v[8]; uint32_t bad; int it = 0;
        do {
          bad = 0;
#pragma unroll
          for (int u = 0; u < 8; u++) v[u] = ld_tag4(g_hst + row0 * 8 + u * 64 + 2 * lane);
#pragma unroll
          for (int u = 0; u < 8; u++) bad |= tag_bad(v[u], tag);
          spin_check(it);
        } while (bad);
        float m0 = 0.f, m1 = 0.f, q0 = 0.f, q1 = 0.f;
#pragma unroll
        for (int u = 0; u < 8; u++) { m0 += v[u].x; m1 += v[u].z; }
        m0 *= 0.125f; m1 *= 0.125f;
#pragma unroll
        for (int u = 0; u < 8; u++) { q0 += fmaf(128.f * (v[u].x - m0), v[u].x - m0, v[u].y); q1 += fmaf(128.f * (v[u].z - m1), v[u].z - m1, v[u].w); }
        sts128(c.sb + OFF_ST + (64 * a + 2 * lane) * 8, __float_as_uint(m0), __float_as_uint(rsqrtf(fmaxf(q0, 0.f) * (1.f / D_) + 1e-5f)),
               __float_as_uint(m1), __float_as_uint(rsqrtf(fmaxf(q1, 0.f) * (1.f / D_) + 1e-5f)));
      }
    }
    const int nl = r == 1 ? 16 : r == 3 ? 24 : 32, dcol = 256 * (r & 1) + 4 * (nl * a + lane);
    if (lane < nl) cs_gather(c, dcol + 384 * (r >> 1), dcol);
    __syncwarp();
    if (lane == 0) { mbar_arrive(c.bar + 8 * (B_RDY0 + (r & 1))); if (lead) PROF(7 + r); }
    if (r == 1) {
      named_sync(5 + a, 64);
      const int hx = (c.i * 8 + c.j) * 2 + a;
      if (lane == 0 && c.i < 15) {
#pragma unroll
        for (int t = 0; t < 2; t++) asm volatile("cp.async.bulk.global.shared::cta.bulk_group [%0], [%1], 2048;" ::"l"(g_halo + hx * 256 + t * 128), "r"(mystg + t * 8192) : "memory");
        bulk_commit(); bulk_wait_all();
        asm volatile("red.relaxed.gpu.global.add.u32 [%0], 1;" ::"l"(g_hflag + hx * HFS) : "memory");
      }
      __syncwarp();
      if (c.i == 0) {
#pragma unroll
        for (int u = 0; u < 8; u++) sts128(mystg + (u >> 2) * 8192 + (u & 3) * 512 + lane * 16, 0, 0, 0, 0);
        __syncwarp();
      }
      if (lane == 0) {
        const uint32_t bH = c.bar + 8 * (B_HALO + a);
        if (c.i == 0) mbar_arrive(bH);
        else {
          uint32_t v; int it = 0;
          do { asm volatile("ld.acquire.gpu.global.u32 %0, [%1];" : "=r"(v) : "l"(g_hflag + (hx - 16) * HFS) : "memory"); spin_check(it); } while ((int)(v - c.ep1) < 0);
          fence_async_global();
          mbar_expect_tx(bH, 4096);
#pragma unroll
          for (int t = 0; t < 2; t++)
            asm volatile("cp.async.bulk.shared::cluster.global.mbarrier::complete_tx::bytes [%0], [%1], 2048, [%2];" ::"r"(mystg + t * 8192), "l"(g_halo + (hx - 16) * 256 + t * 128), "r"(bH) : "memory");
        }
        if (lead) PROF(11);
#pragma unroll 1
        for (int t = 0; t < 2; t++) {
          mbar_wait(t ? bSF : c.bar + 8 * (B_SFA + a), 0);
          tma2d_st(&p.mO, mystg + t * 8192, 128 * c.j + 64 * t, row0); bulk_commit();
          if (lead) PROF(13 + 3 * t);
          bulk_wait_all(); flag_add(F_O + c.i * 4 + 2 * t + a);
          if (lead) PROF(14 + 3 * t);
        }
        wait_progress(c, XR + a * XRA);
        mbar_expect_tx(bSE, 16384);
        tma3d(mystg, &p.mX, bSE, 128 * c.j, a, 64 * c.i); tma3d(mystg + 8192, &p.mX, bSE, 128 * c.j + 64, a, 64 * c.i);
      }
      named_sync(3, 64);
    }
    if (r >= 2) {
      if (lane == 0) {
        const int col = 448 * c.j + 256 * (r - 2);
        mbar_wait(bSF, r & 1);
#pragma unroll 1
        for (int x = r - 2; x < 4; x++) {
          wait_progress(c, r == 2 ? 64 + PACE3 + 2 * x + a : 80 + PACE4 + PACE * (2 * (x - 1) + a));
          tma2d_st(&p.mH1, x < 2 ? spare + x * 16384 + a * 8192 : mystg + (x - 2) * 8192, col + (x < 2 ? (x + 4 - r) * 64 : (x - 2) * 64), row0);
          bulk_commit();
          if (x == 7 - 2 * r) { bulk_wait_read(); mbar_arrive(bSE); }
        }
        bulk_wait_all(); flag_add(F_H1 + c.i * 4 + 2 * (r - 2) + a);
        if (lead) PROF(20 + r);
        if (r == 3) { mbar_expect_tx(bA, 16384); tma2d(mystg, &p.mH, bA, 128 * c.j, row0); tma2d(mystg + 8192, &p.mH, bA, 128 * c.j + 64, row0); }
      }
      __syncwarp();
    }
  }
}

__device__ __forceinline__ void helper_unit(int g, int& j, int& u) {
  const int x = g >> 3;
  j = x < 16 ? x >> 1 : x < 48 ? (x - 16) >> 2 : (x - 48) / 3;
  u = 8 * (x < 16 ? 4 + (x & 1) : x < 48 ? 6 + (x & 3) : 10 + x % 3) + (g & 7);
}
__device__ __forceinline__ void helper_warp(const Params& p, const Ctx& c, int g0, int warp, int lane) {
  const uint32_t buf = c.sb + warp * 16384, bar = c.bar + 8 * (warp < 8 ? warp : warp + B_SEMPTY - 8);
#pragma unroll 1
  for (int t = 0; t < 12; t++) {
    int j, u;
    if (t < 11 && lane == 0) { helper_unit(g0 + 48 * t + 48, j, u); unit_load<true>(p, j, u, 0, 0); }
    helper_unit(g0 + 48 * t, j, u);
    if (lane == 0) unit_load<false>(p, j, u, buf, bar);
    mbar_wait(bar, t & 1);
    unit_sum(j, c.ep1 & 3, u, buf, lane);
  }
}

__device__ __forceinline__ uint32_t load_epoch() {
  uint32_t ctr;
  asm volatile("ld.relaxed.gpu.global.u32 %0, [%1];" : "=r"(ctr) : "l"(&g_ctr) : "memory");
  return (ctr >> 7) + 1;
}

__global__ void __cluster_dims__(2, 1, 1) __launch_bounds__(384, 1) fused_block_kernel(const __grid_constant__ Params p) {
  extern __shared__ __align__(1024) uint8_t smem_raw[];
  Ctx c;
  c.sb = (uint32_t)__cvta_generic_to_shared(smem_raw);
  c.bar = c.sb + OFF_BAR;
  c.rank = blockIdx.x & 1;
  int cl = (blockIdx.x >> 1) + (gridDim.x == 4 ? 64 : 0);
  if (gridDim.x == 132) {
    uint32_t t; asm("mov.u32 %0, %%smid;" : "=r"(t));
    t >>= 1;
    cl = t < 32 ? (t & 7) * 8 + (t >> 3) : t < 60 ? (1 + (t - 32) % 7) * 8 + 4 + (t - 32) / 7 : t < 62 ? t + 4 : t - 58;
  }
  const bool helper = cl >= 64;
  c.i = cl & 15; c.j = ((cl >> 4) & 3) * 2 + c.rank;
  const int warp = __shfl_sync(~0u, threadIdx.x >> 5, 0), lane = threadIdx.x & 31;
  if (warp == 8 && lane == 0) {
    PROF(0);
    map_prefetch(&p.mWkv); map_prefetch(&p.mX);
#pragma unroll
    for (int s = 0; s < 4; s++) mbar_init(c.bar + 8 * s, 1);
    fence_async_smem();
    if (!helper) produce_b<0>(p, c, 0, NB0);
    asm volatile("fence.mbarrier_init.release.cluster;" ::: "memory");
  }
  if (warp == 9 && lane == 0) {
    asm volatile("{\n.reg .pred p;\nsetp.ne.u32 p, %0, %1;\n@p trap;\n}\n" ::"r"(c.sb & 0x3FFFF), "n"(SMEM_BASE));
#pragma unroll
    for (int s = 4; s < B_NUM; s++) mbar_init(c.bar + 8 * s, (s < B_EMPTY || s >= B_SEMPTY) ? 1 : (s >= B_RDY0 ? 2 : 4));
    set_progress(c, -1); __threadfence_block();
    asm volatile("fence.mbarrier_init.release.cluster;" ::: "memory");
    fence_async_smem();
  }
  __syncwarp();
  asm volatile("barrier.cluster.arrive.relaxed.aligned;" ::: "memory");
  asm volatile("barrier.cluster.wait.acquire.aligned;" ::: "memory");
  if (helper) {
    c.ep1 = load_epoch();
    helper_warp(p, c, ((cl & 1) * 2 + c.rank) * 12 + warp, warp, lane);
  } else if (warp >= 8) {
    asm volatile("setmaxnreg.dec.sync.aligned.u32 88;");
    if (warp == 8) {
      if (lane == 0) {
        PROF(1);
        produce_b<0>(p, c, NB0, 16); produce_b<1>(p, c, 0, 16); produce_b<2>(p, c, 0, 16); produce_b<3>(p, c, 0, 16); produce_b<4>(p, c, 0, 16); produce_b<5>(p, c, 0, 56);
        asm volatile("red.relaxed.gpu.global.add.u32 [%0], 1;" ::"l"(&g_ctr) : "memory");
      }
    } else if (warp == 9) {
      if (lane == 0) {
        bool seen = false;
        produce_a<0>(p, c, seen); c.ep1 = load_epoch(); produce_a<1>(p, c, seen); produce_a<2>(p, c, seen); produce_a<3>(p, c, seen); produce_a<4>(p, c, seen); produce_a<5>(p, c, seen);
      }
    } else {
      c.ep1 = load_epoch();
      aux_warp(p, c, warp - 10, lane);
    }
  } else {
    asm volatile("setmaxnreg.inc.sync.aligned.u32 208;");
    c.ep1 = load_epoch();
    Con k;
    k.wg = warp >> 2; k.w = warp & 3; k.lane = lane; k.spin = 0;
    k.do_rel = (threadIdx.x & 127) < 2;
    k.rel = mapa(c.bar + 8 * B_EMPTY, threadIdx.x & 1);
    k.stg = c.sb + OFF_STG + k.wg * 16384;
    k.da = ((SMEM_BASE >> 4) | (1u << 16)) + k.wg * 512;
    uint32_t kv[32][2], res[32]; float accq[64];
    {
      float acc[128]; Pre pr;
      const int rb = 16 * c.j + 2 * warp + (lane >> 4);
      const uint4* xr = reinterpret_cast<const uint4*>(p.x + (size_t)(128 * c.i + rb) * D_) + (lane & 15);
      uint4 xv[8];
      ISSUE0(0, acc);
#pragma unroll
      for (int e = 0; e < 8; e++) xv[e] = ldcg128(xr + 16 * e);
      steps<0>(acc, c, k, 1, XST);
      ISSUE(0, acc, XST);
      const float sh = XSH ? __shfl_sync(~0u, bf_lo(xv[0].x), lane & 16) : 0.f;
      float s1[2] = {0.f, 0.f}, s2[2] = {0.f, 0.f};
#pragma unroll
      for (int e = 0; e < 8; e++) {
        { acc_stat(xv[e].x, sh, s1[0], s2[0]); acc_stat(xv[e].y, sh, s1[1], s2[1]); acc_stat(xv[e].z, sh, s1[0], s2[0]); acc_stat(xv[e].w, sh, s1[1], s2[1]); }
        if (XS3 ? (e & 3) == 3 : e == 4) { asm volatile("" : "+f"(s1[0]), "+f"(s1[1]), "+f"(s2[0]), "+f"(s2[1])); retire<0>(k, XST + (XS3 ? e >> 2 : 0)); ISSUE(0, acc, XST + 1 + (XS3 ? e >> 2 : 0)); }
      }
      float t1 = s1[0] + s1[1], t2 = s2[0] + s2[1];
#pragma unroll
      for (int o = 1; o < 16; o <<= 1) { t1 += __shfl_xor_sync(~0u, t1, o); t2 += __shfl_xor_sync(~0u, t2, o); }
      t1 *= 1.f / D_;
      if ((lane & 15) < 2) st_tag2(g_xst + (64 * c.i + (rb >> 1)) * 4 + 2 * (lane & 1) + (rb & 1), sh + t1, rsqrtf(fmaxf(fmaf(-t1, t1, t2 * (1.f / D_)), 0.f) + 1e-5f), c.ep1 & 3);
      if (threadIdx.x == 0) PROF(5);
      retire<0>(k, XST + 1 + XS3);
      steps<0>(acc, c, k, XST + 2 + XS3, 15);
      LAST(0, acc, (STAG & 1));
      qkv_pack<0, 0, SH0 ? 8 : 16>(kv, acc, pr, c, k);
      ISSUE0(1, accq);
      if (SH0) {
        qkv_pack<0, 8, 10>(kv, acc, pr, c, k);
        ISSUE(1, accq, 1); qkv_pack<0, 10, 12>(kv, acc, pr, c, k); retire<1>(k, 1);
        ISSUE(1, accq, 2); qkv_pack<0, 12, 14>(kv, acc, pr, c, k); retire<1>(k, 2);
        ISSUE(1, accq, 3); qkv_pack<0, 14, 16>(kv, acc, pr, c, k); retire<1>(k, 3);
      }
      if (k.do_rel) PROF(32 + 32 * k.wg + 2);
    }
    {
      float (&acc)[64] = accq; Pre pr; uint32_t q[16][2];
      constexpr int M = 1 + 3 * SH0;
      ISSUE(1, acc, M);
#pragma unroll
      for (int t = 16; t < 32; t++) kv[t][1] = movm(kv[t][1]);
      retire<1>(k, M);
      ISSUE(1, acc, M + 1); halo_publish<0>(kv, c, k); retire<1>(k, M + 1);
      ISSUE(1, acc, M + 2); halo_publish<1>(kv, c, k); retire<1>(k, M + 2);
      if (MV0) {
        ISSUE(1, acc, M + 3);
#pragma unroll
        for (int t = 16; t < 24; t++) kv[t][0] = movm(kv[t][0]);
        retire<1>(k, M + 3);
        ISSUE(1, acc, M + 4);
#pragma unroll
        for (int t = 24; t < 32; t++) kv[t][0] = movm(kv[t][0]);
        retire<1>(k, M + 4);
      }
      steps<1>(acc, c, k, M + 3 + 2 * MV0, 15);
      ISSUE(1, acc, 15); pre_load<1>(pr, c, k);
      const float sc0 = pr.s0.y * 0.25503487f, sc1 = pr.s1.y * 0.25503487f;
      const float lmask = -1.4426950408889634e9f * rcp(sc0);
      Att s0, s1;
      att_halo<0>(s0, k);
      retire<1>(k, 15);
      mbar_wait_u(c.bar + 8 * (B_EMPTY + 5), 1, k.spin);
      finish<1>(k);
      qkv_pack<1, 0, 4>(q, acc, pr, c, k);
      att_qk<0>(s0, q, kv, lmask, c, k); att_soft(s0, sc0, sc1, k); att_pv<0>(s0, kv);
      att_out<0>(s0, res, c, k);
      att_halo<1>(s1, k);
      qkv_pack<1, 4, 8>(q, acc, pr, c, k);
      att_qk<1>(s1, q, kv, lmask, c, k); att_soft(s1, sc0, sc1, k); att_pv<1>(s1, kv);
      att_out<1>(s1, res + 16, c, k);
      if (k.do_rel) PROF(32 + 32 * k.wg + 5);
    }
    {
      float acc[64];
      ISSUE_RS(2, acc, res);
      steps<2>(acc, c, k, 2, 15 - PREU);
      ISSUE(2, acc, 15 - PREU);
      float rf[64];
      res_load(res, c.bar + 8 * (B_SEMPTY + k.wg), 0, k); res_unpack(rf, res);
      if (PREU) { retire<2>(k, 14); ISSUE(2, acc, 15); }
      retire<2>(k, 15);
      finish<2>(k);
      epi_res<0>(acc, rf, res, 1.f, 1.f, k);
      handoff(c, k, B_SFA);
      epi_res<1>(acc, rf, res, 1.f, 1.f, k);
      handoff(c, k);
      if (k.do_rel) PROF(32 + 32 * k.wg + 8);
    }
    {
      float acc4[96], acc[64]; Pre pr;
      {
        float acc3[128];
        ISSUE_RS(3, acc3, res);
        ISSUE(3, acc3, 2); retire<3>(k, 2);
        float s1[2] = {0.f, 0.f}, s2[2] = {0.f, 0.f};
        ISSUE(3, acc3, 3);
#pragma unroll
        for (int e = 0; e < 32; e++) {
          acc_stat(res[e], 0.f, s1[e & 1], s2[e & 1]);
          if (e == 19) { asm volatile("" : "+f"(s1[0]), "+f"(s1[1]), "+f"(s2[0]), "+f"(s2[1])); retire<3>(k, 3); ISSUE(3, acc3, 4); }
        }
        const bool odd = lane & 1;
        float t1 = (odd ? s1[1] : s1[0]) + __shfl_xor_sync(~0u, odd ? s1[0] : s1[1], 1), t2 = (odd ? s2[1] : s2[0]) + __shfl_xor_sync(~0u, odd ? s2[0] : s2[1], 1);
        t1 += __shfl_xor_sync(~0u, t1, 2); t2 += __shfl_xor_sync(~0u, t2, 2);
        if (!(lane & 2)) st_tag2(g_hst + (128 * c.i + 64 * k.wg) * 8 + c.j * 64 + k.w * 16 + (lane >> 2) + 8 * (lane & 1), t1 * (1.f / 128), fmaf(-t1 * (1.f / 128), t1, t2), c.ep1 & 3);
        retire<3>(k, 4);
        steps<3>(acc3, c, k, 5, 15);
        LAST(3, acc3, (STAG & 2));
        if (SH3) {
          epi_ffn1<4, 0, 8>(acc3, pr, c, k);
          ISSUE0(4, acc4); epi_ffn1<4, 8, 10>(acc3, pr, c, k);
          ISSUE(4, acc4, 1); epi_ffn1<4, 10, 13>(acc3, pr, c, k); retire<4>(k, 1);
          ISSUE(4, acc4, 2); epi_ffn1<4, 13, 16>(acc3, pr, c, k); retire<4>(k, 2);
        } else {
          epi_ffn1<4, 0, 16>(acc3, pr, c, k);
          ISSUE0(4, acc4);
        }
        if (k.do_rel) PROF(32 + 32 * k.wg + 11);
      }
      steps<4>(acc4, c, k, SH3 ? 3 : 1, 15);
      ISSUE(4, acc4, 15); pre_load<4>(pr, c, k); retire<4>(k, 15);
      if (SH4) {
        ISSUE0(5, acc);
        finish<4, 1>(k);
        reg_fence(acc4);
        ISSUE(5, acc, 1); epi_ffn1<3, 0, 2>(acc4, pr, c, k); retire<5>(k, 1);
        ISSUE(5, acc, 2); epi_ffn1<3, 2, 4>(acc4, pr, c, k); retire<5>(k, 2);
        ISSUE(5, acc, 3); epi_ffn1<3, 4, 6>(acc4, pr, c, k); retire<5>(k, 3);
        ISSUE(5, acc, 4); epi_ffn1<3, 6, 8>(acc4, pr, c, k); retire<5>(k, 4);
        ISSUE(5, acc, 5); epi_ffn1<3, 8, 10>(acc4, pr, c, k); retire<5>(k, 5);
        ISSUE(5, acc, 6); epi_ffn1<3, 10, 12>(acc4, pr, c, k); retire<5>(k, 6);
      } else {
        finish<4>(k);
        epi_ffn1<3, 0, 12>(acc4, pr, c, k);
        ISSUE0(5, acc);
      }
      if (k.do_rel) PROF(32 + 32 * k.wg + 14);
      steps<5>(acc, c, k, SH4 ? 7 : 1, 55 - PREU);
      ISSUE(5, acc, 55 - PREU);
      const uint32_t sta = c.sb + OFF_ST + (k.wg * 64 + k.w * 16 + (lane >> 2)) * 8;
      const float sc0 = lds64f(sta).y, sc1 = lds64f(sta + 64).y;
      float rf[64];
      res_load(res, c.bar + 8 * (B_AUX + k.wg), 1, k); res_unpack(rf, res);
      if (PREU) ISSUE(5, acc, 55);
      spin_check(k.spin);
      finish<5>(k);
      epi_res<0>(acc, rf, res, sc0, sc1, k);
      fence_async_smem(); __syncwarp();
      if (lane == 0) tma3d_st(&p.mOut, k.stg + k.w * 2048, 128 * c.j, k.wg, 64 * c.i + 16 * k.w);
      epi_res<1>(acc, rf, res, sc0, sc1, k);
      fence_async_smem(); __syncwarp();
      if (k.do_rel) PROF(32 + 32 * k.wg + 17);
      if (lane == 0) { tma3d_st(&p.mOut, k.stg + 8192 + k.w * 2048, 128 * c.j + 64, k.wg, 64 * c.i + 16 * k.w); bulk_commit(); bulk_wait_read(); }
      if (k.do_rel) PROF(32 + 32 * k.wg + 18);
    }
  }
}

typedef CUresult (*EncFn)(CUtensorMap*, CUtensorMapDataType, cuuint32_t, void*, const cuuint64_t*, const cuuint64_t*, const cuuint32_t*,
                          const cuuint32_t*, CUtensorMapInterleave, CUtensorMapSwizzle, CUtensorMapL2promotion, CUtensorMapFloatOOBfill);

void enc(EncFn f, CUtensorMap* m, const void* ptr, int rank, cuuint64_t d0, cuuint64_t d1, cuuint64_t d2, cuuint64_t s1, cuuint64_t s2,
         cuuint32_t b0, cuuint32_t b1, cuuint32_t b2, CUtensorMapSwizzle sw = CU_TENSOR_MAP_SWIZZLE_128B) {
  const cuuint64_t dims[3] = {d0, d1, d2}, str[2] = {s1, s2};
  const cuuint32_t box[3] = {b0, b1, b2}, es[3] = {1, 1, 1};
  f(m, CU_TENSOR_MAP_DATA_TYPE_BFLOAT16, rank, const_cast<void*>(ptr), dims, str, box, es, CU_TENSOR_MAP_INTERLEAVE_NONE,
    sw, CU_TENSOR_MAP_L2_PROMOTION_L2_256B, CU_TENSOR_MAP_FLOAT_OOB_FILL_NONE);
}

}

extern "C" void kernel_launch(void* const* d_in, const int* in_sizes, int n_in, void* d_out, int out_size) {
  (void)in_sizes; (void)n_in; (void)out_size;
  const void *x = d_in[0], *wqkv = d_in[1], *wo = d_in[2], *w1 = d_in[4], *w2 = d_in[5];
  EncFn f = nullptr;
  cudaDriverEntryPointQueryResult qr;
  cudaGetDriverEntryPoint("cuTensorMapEncodeTiled", (void**)&f, cudaEnableDefault, &qr);
  void *po, *ph, *ph1;
  cudaGetSymbolAddress(&po, g_o); cudaGetSymbolAddress(&ph, g_h); cudaGetSymbolAddress(&ph1, g_h1);
  Params p;
  enc(f, &p.mX, x, 3, D_, 2, S_ / 2, D_ * 2, D_ * 4, 64, 1, 64);
  enc(f, &p.mOut, d_out, 3, D_, 2, S_ / 2, D_ * 2, D_ * 4, 64, 1, 16);
  enc(f, &p.mCq, wqkv, 2, 3 * D_, D_, 1, 3 * D_ * 2, 0, 64, 128, 1, CU_TENSOR_MAP_SWIZZLE_NONE);
  enc(f, &p.mC1, w1, 2, F_, D_, 1, F_ * 2, 0, 64, 128, 1, CU_TENSOR_MAP_SWIZZLE_NONE);
  {
    const cuuint64_t dims[4] = {64, D_, D_ / 64, 3}, str[3] = {3 * D_ * 2, 128, D_ * 2};
    const cuuint32_t box[4] = {64, 64, 2, 2}, es[4] = {1, 1, 1, 1};
    f(&p.mWkv, CU_TENSOR_MAP_DATA_TYPE_BFLOAT16, 4, const_cast<void*>(wqkv), dims, str, box, es, CU_TENSOR_MAP_INTERLEAVE_NONE,
      CU_TENSOR_MAP_SWIZZLE_128B, CU_TENSOR_MAP_L2_PROMOTION_L2_256B, CU_TENSOR_MAP_FLOAT_OOB_FILL_NONE);
  }
  enc(f, &p.mWq, wqkv, 3, 64, D_, D_ / 64, 3 * D_ * 2, 128, 64, 64, 2);
  enc(f, &p.mWo, wo, 3, 64, D_, D_ / 64, D_ * 2, 128, 64, 64, 2);
  enc(f, &p.mW1a, w1, 3, 64, D_, F_ / 64, F_ * 2, 128, 64, 64, 4);
  enc(f, &p.mW1b, w1, 3, 64, D_, F_ / 64, F_ * 2, 128, 64, 64, 3);
  enc(f, &p.mW2, w2, 3, 64, F_, D_ / 64, D_ * 2, 128, 64, 64, 2);
  enc(f, &p.mO, po, 2, D_, S_, 1, D_ * 2, 0, 64, 64, 1);
  enc(f, &p.mH, ph, 2, D_, S_, 1, D_ * 2, 0, 64, 64, 1);
  enc(f, &p.mH1, ph1, 2, F_, S_, 1, F_ * 2, 0, 64, 64, 1);
  p.x = (const bf16*)x;
  cudaFuncSetAttribute(fused_block_kernel, cudaFuncAttributeMaxDynamicSharedMemorySize, SMEM_BYTES);
  cudaLaunchConfig_t cfg = {};
  cudaLaunchAttribute at;
  at.id = cudaLaunchAttributeClusterDimension; at.val.clusterDim.x = 2; at.val.clusterDim.y = 1; at.val.clusterDim.z = 1;
  cfg.gridDim = dim3(132); cfg.blockDim = dim3(384); cfg.dynamicSmemBytes = SMEM_BYTES; cfg.attrs = &at; cfg.numAttrs = 1;
  int ncl = 0, dev = 0, nsm = 0;
  cudaGetDevice(&dev);
  cudaDeviceGetAttribute(&nsm, cudaDevAttrMultiProcessorCount, dev);
  cudaOccupancyMaxActiveClusters(&ncl, fused_block_kernel, &cfg);
  if (ncl == 66 && nsm == 132) {
    fused_block_kernel<<<132, 384, SMEM_BYTES>>>(p);
  } else {
    fused_block_kernel<<<4, 384, SMEM_BYTES>>>(p);
    fused_block_kernel<<<128, 384, SMEM_BYTES>>>(p);
  }
}
```

```cpp
#include <cuda_runtime.h>
#include <cuda_bf16.h>
#include <cuda.h>
#include <stdint.h>

namespace {

template <int FIRST> __device__ __forceinline__ void wgmma4_n128(float (&d)[64], uint32_t a, uint32_t b) {
#define WGD "{%0, %1, %2, %3, %4, %5, %6, %7, %8, %9, %10, %11, %12, %13, %14, %15, %16, %17, %18, %19, %20, %21, %22, %23, %24, %25, %26, %27, %28, %29, %30, %31, %32, %33, %34, %35, %36, %37, %38, %39, %40, %41, %42, %43, %44, %45, %46, %47, %48, %49, %50, %51, %52, %53, %54, %55, %56, %57, %58, %59, %60, %61, %62, %63}"
  asm volatile("{\n.reg .pred p, q;\n.reg .b64 da, db;\n.reg .b32 x, y;\nsetp.eq.b32 p, %66, 0;\nsetp.eq.b32 q, 0, 0;\n"
    "add.s32 x, %64, 0;\nadd.s32 y, %65, 0;\nmov.b64 da, {x, %67};\nmov.b64 db, {y, %67};\n"
    "wgmma.mma_async.sync.aligned.m64n128k16.f32.bf16.bf16 " WGD ", da, db, p, 1, 1, 0, 1;\n"
    "add.s32 x, %64, 2;\nadd.s32 y, %65, 128;\nmov.b64 da, {x, %67};\nmov.b64 db, {y, %67};\n"
    "wgmma.mma_async.sync.aligned.m64n128k16.f32.bf16.bf16 " WGD ", da, db, q, 1, 1, 0, 1;\n"
    "add.s32 x, %64, 4;\nadd.s32 y, %65, 256;\nmov.b64 da, {x, %67};\nmov.b64 db, {y, %67};\n"
    "wgmma.mma_async.sync.aligned.m64n128k16.f32.bf16.bf16 " WGD ", da, db, q, 1, 1, 0, 1;\n"
    "add.s32 x, %64, 6;\nadd.s32 y, %65, 384;\nmov.b64 da, {x, %67};\nmov.b64 db, {y, %67};\n"
    "wgmma.mma_async.sync.aligned.m64n128k16.f32.bf16.bf16 " WGD ", da, db, q, 1, 1, 0, 1;\n"
    "}\n"
    : "+f"(d[0]), "+f"(d[1]), "+f"(d[2]), "+f"(d[3]), "+f"(d[4]), "+f"(d[5]), "+f"(d[6]), "+f"(d[7]),
      "+f"(d[8]), "+f"(d[9]), "+f"(d[10]), "+f"(d[11]), "+f"(d[12]), "+f"(d[13]), "+f"(d[14]), "+f"(d[15]),
      "+f"(d[16]), "+f"(d[17]), "+f"(d[18]), "+f"(d[19]), "+f"(d[20]), "+f"(d[21]), "+f"(d[22]), "+f"(d[23]),
      "+f"(d[24]), "+f"(d[25]), "+f"(d[26]), "+f"(d[27]), "+f"(d[28]), "+f"(d[29]), "+f"(d[30]), "+f"(d[31]),
      "+f"(d[32]), "+f"(d[33]), "+f"(d[34]), "+f"(d[35]), "+f"(d[36]), "+f"(d[37]), "+f"(d[38]), "+f"(d[39]),
      "+f"(d[40]), "+f"(d[41]), "+f"(d[42]), "+f"(d[43]), "+f"(d[44]), "+f"(d[45]), "+f"(d[46]), "+f"(d[47]),
      "+f"(d[48]), "+f"(d[49]), "+f"(d[50]), "+f"(d[51]), "+f"(d[52]), "+f"(d[53]), "+f"(d[54]), "+f"(d[55]),
      "+f"(d[56]), "+f"(d[57]), "+f"(d[58]), "+f"(d[59]), "+f"(d[60]), "+f"(d[61]), "+f"(d[62]), "+f"(d[63])
    : "r"(a), "r"(b), "n"(FIRST), "r"(0x40000040));
#undef WGD
}

template <int FIRST> __device__ __forceinline__ void wgmma4_n192(float (&d)[96], uint32_t a, uint32_t b) {
#define WGD "{%0, %1, %2, %3, %4, %5, %6, %7, %8, %9, %10, %11, %12, %13, %14, %15, %16, %17, %18, %19, %20, %21, %22, %23, %24, %25, %26, %27, %28, %29, %30, %31, %32, %33, %34, %35, %36, %37, %38, %39, %40, %41, %42, %43, %44, %45, %46, %47, %48, %49, %50, %51, %52, %53, %54, %55, %56, %57, %58, %59, %60, %61, %62, %63, %64, %65, %66, %67, %68, %69, %70, %71, %72, %73, %74, %75, %76, %77, %78, %79, %80, %81, %82, %83, %84, %85, %86, %87, %88, %89, %90, %91, %92, %93, %94, %95}"
  asm volatile("{\n.reg .pred p, q;\n.reg .b64 da, db;\n.reg .b32 x, y;\nsetp.eq.b32 p, %98, 0;\nsetp.eq.b32 q, 0, 0;\n"
    "add.s32 x, %96, 0;\nadd.s32 y, %97, 0;\nmov.b64 da, {x, %99};\nmov.b64 db, {y, %99};\n"
    "wgmma.mma_async.sync.aligned.m64n192k16.f32.bf16.bf16 " WGD ", da, db, p, 1, 1, 0, 1;\n"
    "add.s32 x, %96, 2;\nadd.s32 y, %97, 128;\nmov.b64 da, {x, %99};\nmov.b64 db, {y, %99};\n"
    "wgmma.mma_async.sync.aligned.m64n192k16.f32.bf16.bf16 " WGD ", da, db, q, 1, 1, 0, 1;\n"
    "add.s32 x, %96, 4;\nadd.s32 y, %97, 256;\nmov.b64 da, {x, %99};\nmov.b64 db, {y, %99};\n"
    "wgmma.mma_async.sync.aligned.m64n192k16.f32.bf16.bf16 " WGD ", da, db, q, 1, 1, 0, 1;\n"
    "add.s32 x, %96, 6;\nadd.s32 y, %97, 384;\nmov.b64 da, {x, %99};\nmov.b64 db, {y, %99};\n"
    "wgmma.mma_async.sync.aligned.m64n192k16.f32.bf16.bf16 " WGD ", da, db, q, 1, 1, 0, 1;\n"
    "}\n"
    : "+f"(d[0]), "+f"(d[1]), "+f"(d[2]), "+f"(d[3]), "+f"(d[4]), "+f"(d[5]), "+f"(d[6]), "+f"(d[7]),
      "+f"(d[8]), "+f"(d[9]), "+f"(d[10]), "+f"(d[11]), "+f"(d[12]), "+f"(d[13]), "+f"(d[14]), "+f"(d[15]),
      "+f"(d[16]), "+f"(d[17]), "+f"(d[18]), "+f"(d[19]), "+f"(d[20]), "+f"(d[21]), "+f"(d[22]), "+f"(d[23]),
      "+f"(d[24]), "+f"(d[25]), "+f"(d[26]), "+f"(d[27]), "+f"(d[28]), "+f"(d[29]), "+f"(d[30]), "+f"(d[31]),
      "+f"(d[32]), "+f"(d[33]), "+f"(d[34]), "+f"(d[35]), "+f"(d[36]), "+f"(d[37]), "+f"(d[38]), "+f"(d[39]),
      "+f"(d[40]), "+f"(d[41]), "+f"(d[42]), "+f"(d[43]), "+f"(d[44]), "+f"(d[45]), "+f"(d[46]), "+f"(d[47]),
      "+f"(d[48]), "+f"(d[49]), "+f"(d[50]), "+f"(d[51]), "+f"(d[52]), "+f"(d[53]), "+f"(d[54]), "+f"(d[55]),
      "+f"(d[56]), "+f"(d[57]), "+f"(d[58]), "+f"(d[59]), "+f"(d[60]), "+f"(d[61]), "+f"(d[62]), "+f"(d[63]),
      "+f"(d[64]), "+f"(d[65]), "+f"(d[66]), "+f"(d[67]), "+f"(d[68]), "+f"(d[69]), "+f"(d[70]), "+f"(d[71]),
      "+f"(d[72]), "+f"(d[73]), "+f"(d[74]), "+f"(d[75]), "+f"(d[76]), "+f"(d[77]), "+f"(d[78]), "+f"(d[79]),
      "+f"(d[80]), "+f"(d[81]), "+f"(d[82]), "+f"(d[83]), "+f"(d[84]), "+f"(d[85]), "+f"(d[86]), "+f"(d[87]),
      "+f"(d[88]), "+f"(d[89]), "+f"(d[90]), "+f"(d[91]), "+f"(d[92]), "+f"(d[93]), "+f"(d[94]), "+f"(d[95])
    : "r"(a), "r"(b), "n"(FIRST), "r"(0x40000040));
#undef WGD
}

template <int FIRST> __device__ __forceinline__ void wgmma4_n256(float (&d)[128], uint32_t a, uint32_t b) {
#define WGD "{%0, %1, %2, %3, %4, %5, %6, %7, %8, %9, %10, %11, %12, %13, %14, %15, %16, %17, %18, %19, %20, %21, %22, %23, %24, %25, %26, %27, %28, %29, %30, %31, %32, %33, %34, %35, %36, %37, %38, %39, %40, %41, %42, %43, %44, %45, %46, %47, %48, %49, %50, %51, %52, %53, %54, %55, %56, %57, %58, %59, %60, %61, %62, %63, %64, %65, %66, %67, %68, %69, %70, %71, %72, %73, %74, %75, %76, %77, %78, %79, %80, %81, %82, %83, %84, %85, %86, %87, %88, %89, %90, %91, %92, %93, %94, %95, %96, %97, %98, %99, %100, %101, %102, %103, %104, %105, %106, %107, %108, %109, %110, %111, %112, %113, %114, %115, %116, %117, %118, %119, %120, %121, %122, %123, %124, %125, %126, %127}"
  asm volatile("{\n.reg .pred p, q;\n.reg .b64 da, db;\n.reg .b32 x, y;\nsetp.eq.b32 p, %130, 0;\nsetp.eq.b32 q, 0, 0;\n"
    "add.s32 x, %128, 0;\nadd.s32 y, %129, 0;\nmov.b64 da, {x, %131};\nmov.b64 db, {y, %131};\n"
    "wgmma.mma_async.sync.aligned.m64n256k16.f32.bf16.bf16 " WGD ", da, db, p, 1, 1, 0, 1;\n"
    "add.s32 x, %128, 2;\nadd.s32 y, %129, 128;\nmov.b64 da, {x, %131};\nmov.b64 db, {y, %131};\n"
    "wgmma.mma_async.sync.aligned.m64n256k16.f32.bf16.bf16 " WGD ", da, db, q, 1, 1, 0, 1;\n"
    "add.s32 x, %128, 4;\nadd.s32 y, %129, 256;\nmov.b64 da, {x, %131};\nmov.b64 db, {y, %131};\n"
    "wgmma.mma_async.sync.aligned.m64n256k16.f32.bf16.bf16 " WGD ", da, db, q, 1, 1, 0, 1;\n"
    "add.s32 x, %128, 6;\nadd.s32 y, %129, 384;\nmov.b64 da, {x, %131};\nmov.b64 db, {y, %131};\n"
    "wgmma.mma_async.sync.aligned.m64n256k16.f32.bf16.bf16 " WGD ", da, db, q, 1, 1, 0, 1;\n"
    "}\n"
    : "+f"(d[0]), "+f"(d[1]), "+f"(d[2]), "+f"(d[3]), "+f"(d[4]), "+f"(d[5]), "+f"(d[6]), "+f"(d[7]),
      "+f"(d[8]), "+f"(d[9]), "+f"(d[10]), "+f"(d[11]), "+f"(d[12]), "+f"(d[13]), "+f"(d[14]), "+f"(d[15]),
      "+f"(d[16]), "+f"(d[17]), "+f"(d[18]), "+f"(d[19]), "+f"(d[20]), "+f"(d[21]), "+f"(d[22]), "+f"(d[23]),
      "+f"(d[24]), "+f"(d[25]), "+f"(d[26]), "+f"(d[27]), "+f"(d[28]), "+f"(d[29]), "+f"(d[30]), "+f"(d[31]),
      "+f"(d[32]), "+f"(d[33]), "+f"(d[34]), "+f"(d[35]), "+f"(d[36]), "+f"(d[37]), "+f"(d[38]), "+f"(d[39]),
      "+f"(d[40]), "+f"(d[41]), "+f"(d[42]), "+f"(d[43]), "+f"(d[44]), "+f"(d[45]), "+f"(d[46]), "+f"(d[47]),
      "+f"(d[48]), "+f"(d[49]), "+f"(d[50]), "+f"(d[51]), "+f"(d[52]), "+f"(d[53]), "+f"(d[54]), "+f"(d[55]),
      "+f"(d[56]), "+f"(d[57]), "+f"(d[58]), "+f"(d[59]), "+f"(d[60]), "+f"(d[61]), "+f"(d[62]), "+f"(d[63]),
      "+f"(d[64]), "+f"(d[65]), "+f"(d[66]), "+f"(d[67]), "+f"(d[68]), "+f"(d[69]), "+f"(d[70]), "+f"(d[71]),
      "+f"(d[72]), "+f"(d[73]), "+f"(d[74]), "+f"(d[75]), "+f"(d[76]), "+f"(d[77]), "+f"(d[78]), "+f"(d[79]),
      "+f"(d[80]), "+f"(d[81]), "+f"(d[82]), "+f"(d[83]), "+f"(d[84]), "+f"(d[85]), "+f"(d[86]), "+f"(d[87]),
      "+f"(d[88]), "+f"(d[89]), "+f"(d[90]), "+f"(d[91]), "+f"(d[92]), "+f"(d[93]), "+f"(d[94]), "+f"(d[95]),
      "+f"(d[96]), "+f"(d[97]), "+f"(d[98]), "+f"(d[99]), "+f"(d[100]), "+f"(d[101]), "+f"(d[102]), "+f"(d[103]),
      "+f"(d[104]), "+f"(d[105]), "+f"(d[106]), "+f"(d[107]), "+f"(d[108]), "+f"(d[109]), "+f"(d[110]), "+f"(d[111]),
      "+f"(d[112]), "+f"(d[113]), "+f"(d[114]), "+f"(d[115]), "+f"(d[116]), "+f"(d[117]), "+f"(d[118]), "+f"(d[119]),
      "+f"(d[120]), "+f"(d[121]), "+f"(d[122]), "+f"(d[123]), "+f"(d[124]), "+f"(d[125]), "+f"(d[126]), "+f"(d[127])
    : "r"(a), "r"(b), "n"(FIRST), "r"(0x40000040));
#undef WGD
}

template <int FIRST> __device__ __forceinline__ void wgmma4(float (&d)[64], const uint32_t* a, uint32_t b) {
#define WGD "{%0, %1, %2, %3, %4, %5, %6, %7, %8, %9, %10, %11, %12, %13, %14, %15, %16, %17, %18, %19, %20, %21, %22, %23, %24, %25, %26, %27, %28, %29, %30, %31, %32, %33, %34, %35, %36, %37, %38, %39, %40, %41, %42, %43, %44, %45, %46, %47, %48, %49, %50, %51, %52, %53, %54, %55, %56, %57, %58, %59, %60, %61, %62, %63}"
  asm volatile("{\n.reg .pred p, q;\n.reg .b64 db;\n.reg .b32 y;\nsetp.eq.b32 p, %81, 0;\nsetp.eq.b32 q, 0, 0;\n"
    "add.s32 y, %80, 0;\nmov.b64 db, {y, %82};\n"
    "wgmma.mma_async.sync.aligned.m64n128k16.f32.bf16.bf16 " WGD ", {%64, %65, %66, %67}, db, p, 1, 1, 1;\n"
    "add.s32 y, %80, 128;\nmov.b64 db, {y, %82};\n"
    "wgmma.mma_async.sync.aligned.m64n128k16.f32.bf16.bf16 " WGD ", {%68, %69, %70, %71}, db, q, 1, 1, 1;\n"
    "add.s32 y, %80, 256;\nmov.b64 db, {y, %82};\n"
    "wgmma.mma_async.sync.aligned.m64n128k16.f32.bf16.bf16 " WGD ", {%72, %73, %74, %75}, db, q, 1, 1, 1;\n"
    "add.s32 y, %80, 384;\nmov.b64 db, {y, %82};\n"
    "wgmma.mma_async.sync.aligned.m64n128k16.f32.bf16.bf16 " WGD ", {%76, %77, %78, %79}, db, q, 1, 1, 1;\n"
    "}\n"
    : "+f"(d[0]), "+f"(d[1]), "+f"(d[2]), "+f"(d[3]), "+f"(d[4]), "+f"(d[5]), "+f"(d[6]), "+f"(d[7]),
      "+f"(d[8]), "+f"(d[9]), "+f"(d[10]), "+f"(d[11]), "+f"(d[12]), "+f"(d[13]), "+f"(d[14]), "+f"(d[15]),
      "+f"(d[16]), "+f"(d[17]), "+f"(d[18]), "+f"(d[19]), "+f"(d[20]), "+f"(d[21]), "+f"(d[22]), "+f"(d[23]),
      "+f"(d[24]), "+f"(d[25]), "+f"(d[26]), "+f"(d[27]), "+f"(d[28]), "+f"(d[29]), "+f"(d[30]), "+f"(d[31]),
      "+f"(d[32]), "+f"(d[33]), "+f"(d[34]), "+f"(d[35]), "+f"(d[36]), "+f"(d[37]), "+f"(d[38]), "+f"(d[39]),
      "+f"(d[40]), "+f"(d[41]), "+f"(d[42]), "+f"(d[43]), "+f"(d[44]), "+f"(d[45]), "+f"(d[46]), "+f"(d[47]),
      "+f"(d[48]), "+f"(d[49]), "+f"(d[50]), "+f"(d[51]), "+f"(d[52]), "+f"(d[53]), "+f"(d[54]), "+f"(d[55]),
      "+f"(d[56]), "+f"(d[57]), "+f"(d[58]), "+f"(d[59]), "+f"(d[60]), "+f"(d[61]), "+f"(d[62]), "+f"(d[63])
    : "r"(a[0]), "r"(a[1]), "r"(a[2]), "r"(a[3]), "r"(a[4]), "r"(a[5]), "r"(a[6]), "r"(a[7]), "r"(a[8]), "r"(a[9]), "r"(a[10]), "r"(a[11]), "r"(a[12]), "r"(a[13]), "r"(a[14]), "r"(a[15]),
      "r"(b), "n"(FIRST), "r"(0x40000040));
#undef WGD
}

template <int FIRST> __device__ __forceinline__ void wgmma4(float (&d)[128], const uint32_t* a, uint32_t b) {
#define WGD "{%0, %1, %2, %3, %4, %5, %6, %7, %8, %9, %10, %11, %12, %13, %14, %15, %16, %17, %18, %19, %20, %21, %22, %23, %24, %25, %26, %27, %28, %29, %30, %31, %32, %33, %34, %35, %36, %37, %38, %39, %40, %41, %42, %43, %44, %45, %46, %47, %48, %49, %50, %51, %52, %53, %54, %55, %56, %57, %58, %59, %60, %61, %62, %63, %64, %65, %66, %67, %68, %69, %70, %71, %72, %73, %74, %75, %76, %77, %78, %79, %80, %81, %82, %83, %84, %85, %86, %87, %88, %89, %90, %91, %92, %93, %94, %95, %96, %97, %98, %99, %100, %101, %102, %103, %104, %105, %106, %107, %108, %109, %110, %111, %112, %113, %114, %115, %116, %117, %118, %119, %120, %121, %122, %123, %124, %125, %126, %127}"
  asm volatile("{\n.reg .pred p, q;\n.reg .b64 db;\n.reg .b32 y;\nsetp.eq.b32 p, %145, 0;\nsetp.eq.b32 q, 0, 0;\n"
    "add.s32 y, %144, 0;\nmov.b64 db, {y, %146};\n"
    "wgmma.mma_async.sync.aligned.m64n256k16.f32.bf16.bf16 " WGD ", {%128, %129, %130, %131}, db, p, 1, 1, 1;\n"
    "add.s32 y, %144, 128;\nmov.b64 db, {y, %146};\n"
    "wgmma.mma_async.sync.aligned.m64n256k16.f32.bf16.bf16 " WGD ", {%132, %133, %134, %135}, db, q, 1, 1, 1;\n"
    "add.s32 y, %144, 256;\nmov.b64 db, {y, %146};\n"
    "wgmma.mma_async.sync.aligned.m64n256k16.f32.bf16.bf16 " WGD ", {%136, %137, %138, %139}, db, q, 1, 1, 1;\n"
    "add.s32 y, %144, 384;\nmov.b64 db, {y, %146};\n"
    "wgmma.mma_async.sync.aligned.m64n256k16.f32.bf16.bf16 " WGD ", {%140, %141, %142, %143}, db, q, 1, 1, 1;\n"
    "}\n"
    : "+f"(d[0]), "+f"(d[1]), "+f"(d[2]), "+f"(d[3]), "+f"(d[4]), "+f"(d[5]), "+f"(d[6]), "+f"(d[7]),
      "+f"(d[8]), "+f"(d[9]), "+f"(d[10]), "+f"(d[11]), "+f"(d[12]), "+f"(d[13]), "+f"(d[14]), "+f"(d[15]),
      "+f"(d[16]), "+f"(d[17]), "+f"(d[18]), "+f"(d[19]), "+f"(d[20]), "+f"(d[21]), "+f"(d[22]), "+f"(d[23]),
      "+f"(d[24]), "+f"(d[25]), "+f"(d[26]), "+f"(d[27]), "+f"(d[28]), "+f"(d[29]), "+f"(d[30]), "+f"(d[31]),
      "+f"(d[32]), "+f"(d[33]), "+f"(d[34]), "+f"(d[35]), "+f"(d[36]), "+f"(d[37]), "+f"(d[38]), "+f"(d[39]),
      "+f"(d[40]), "+f"(d[41]), "+f"(d[42]), "+f"(d[43]), "+f"(d[44]), "+f"(d[45]), "+f"(d[46]), "+f"(d[47]),
      "+f"(d[48]), "+f"(d[49]), "+f"(d[50]), "+f"(d[51]), "+f"(d[52]), "+f"(d[53]), "+f"(d[54]), "+f"(d[55]),
      "+f"(d[56]), "+f"(d[57]), "+f"(d[58]), "+f"(d[59]), "+f"(d[60]), "+f"(d[61]), "+f"(d[62]), "+f"(d[63]),
      "+f"(d[64]), "+f"(d[65]), "+f"(d[66]), "+f"(d[67]), "+f"(d[68]), "+f"(d[69]), "+f"(d[70]), "+f"(d[71]),
      "+f"(d[72]), "+f"(d[73]), "+f"(d[74]), "+f"(d[75]), "+f"(d[76]), "+f"(d[77]), "+f"(d[78]), "+f"(d[79]),
      "+f"(d[80]), "+f"(d[81]), "+f"(d[82]), "+f"(d[83]), "+f"(d[84]), "+f"(d[85]), "+f"(d[86]), "+f"(d[87]),
      "+f"(d[88]), "+f"(d[89]), "+f"(d[90]), "+f"(d[91]), "+f"(d[92]), "+f"(d[93]), "+f"(d[94]), "+f"(d[95]),
      "+f"(d[96]), "+f"(d[97]), "+f"(d[98]), "+f"(d[99]), "+f"(d[100]), "+f"(d[101]), "+f"(d[102]), "+f"(d[103]),
      "+f"(d[104]), "+f"(d[105]), "+f"(d[106]), "+f"(d[107]), "+f"(d[108]), "+f"(d[109]), "+f"(d[110]), "+f"(d[111]),
      "+f"(d[112]), "+f"(d[113]), "+f"(d[114]), "+f"(d[115]), "+f"(d[116]), "+f"(d[117]), "+f"(d[118]), "+f"(d[119]),
      "+f"(d[120]), "+f"(d[121]), "+f"(d[122]), "+f"(d[123]), "+f"(d[124]), "+f"(d[125]), "+f"(d[126]), "+f"(d[127])
    : "r"(a[0]), "r"(a[1]), "r"(a[2]), "r"(a[3]), "r"(a[4]), "r"(a[5]), "r"(a[6]), "r"(a[7]), "r"(a[8]), "r"(a[9]), "r"(a[10]), "r"(a[11]), "r"(a[12]), "r"(a[13]), "r"(a[14]), "r"(a[15]),
      "r"(b), "n"(FIRST), "r"(0x40000040));
#undef WGD
}

#define XSH 1
#define XS3 0
#define MV0 0
#define FS 8
#define STAG 1
#define PREU 0
#define XRA 2
#define XR 37
#define NSL 200
#define NB0 1
#define NA0 1
#define GS 55
#define HFS 8
#define G0 10
#define MPF 55
#define PACEH 1
#define PACE4 6
#define PACE3 2
#define PACE 2
#define ROT3 8
#define M5 15
#define SH4 1
#define SH3 1
#define SH0 1
#define PK0 3
#define AUX_GATE 1
#define XST 8
typedef __nv_bfloat16 bf16;
constexpr int S_ = 2048, D_ = 1024, F_ = 3584;
constexpr int OFF_SPARE = 160 * 1024, OFF_STG = 192 * 1024, OFF_CS = 224 * 1024, OFF_ST = OFF_CS + 1792, OFF_BAR = OFF_ST + 1024;
constexpr int SMEM_BYTES = 232448;
constexpr uint32_t SMEM_BASE = 1024;
enum { B_FULL = 0, B_EMPTY = 8, B_SFULL = 16, B_SFA = 18, B_HALO = 20, B_RDY0 = 22, B_RDY1 = 23, B_SEMPTY = 24, B_AUX = 26, B_NUM = 28, B_PEEK = 28 };
enum { F_O = 0, F_H = 64, F_H1 = 128, F_NUM = 192 };

struct Params {
  CUtensorMap mX, mWkv, mWq, mCq, mC1, mWo, mW1a, mW1b, mW2, mO, mH, mH1, mOut;
  const bf16* x;
};

__device__ __align__(1024) bf16 g_o[S_ * D_];
__device__ __align__(1024) bf16 g_h[S_ * D_];
__device__ __align__(1024) bf16 g_h1[S_ * F_];
__device__ __align__(128) float2 g_xst[2 * S_];
__device__ __align__(128) float2 g_hst[S_ * 8];
__device__ __align__(128) float g_cs[8 * 8 * 832];
__device__ __align__(128) uint4 g_halo[16 * 8 * 2 * 256];
__device__ __align__(128) uint32_t g_hflag[256 * HFS];
__device__ __align__(128) uint32_t g_flag[F_NUM * FS];
__device__ uint32_t g_ctr;
#define PROF(idx) do {} while (0)

constexpr int SPIN_LIMIT = 1 << 22;

__device__ __forceinline__ void mbar_init(uint32_t bar, uint32_t cnt) { asm volatile("mbarrier.init.shared::cta.b64 [%0], %1;" ::"r"(bar), "r"(cnt)); }
__device__ __forceinline__ void mbar_expect_tx(uint32_t bar, uint32_t bytes) { asm volatile("mbarrier.arrive.expect_tx.shared::cta.b64 _, [%0], %1;" ::"r"(bar), "r"(bytes) : "memory"); }
__device__ __forceinline__ void mbar_arrive(uint32_t bar) { asm volatile("mbarrier.arrive.shared::cta.b64 _, [%0];" ::"r"(bar) : "memory"); }
__device__ __forceinline__ void mbar_arrive_cl(uint32_t bar_cluster_addr) { asm volatile("mbarrier.arrive.shared::cluster.b64 _, [%0];" ::"r"(bar_cluster_addr) : "memory"); }
__device__ __forceinline__ uint32_t mapa(uint32_t a, uint32_t cta) { uint32_t r; asm("mapa.shared::cluster.u32 %0, %1, %2;" : "=r"(r) : "r"(a), "r"(cta)); return r; }
__device__ __forceinline__ void spin_check(int& it) { asm volatile("{\n.reg .pred p;\nsetp.gt.s32 p, %0, %1;\n@p trap;\n}\n" ::"r"(++it), "n"(SPIN_LIMIT)); }
__device__ __forceinline__ void mbar_wait(uint32_t bar, uint32_t parity) {
  asm volatile("{\n.reg .pred p;\n.reg .s32 n;\nmov.s32 n, 0;\n"
               "W: mbarrier.try_wait.parity.shared::cta.b64 p, [%0], %1;\n@p bra D;\n"
               "add.s32 n, n, 1;\nsetp.lt.s32 p, n, %2;\n@p bra W;\ntrap;\nD:\n}\n" ::"r"(bar), "r"(parity), "n"(SPIN_LIMIT) : "memory");
}
__device__ __forceinline__ void mbar_wait_u(uint32_t bar, uint32_t parity, int& n) {
  asm volatile("{\n.reg .pred p;\n"
               "W: mbarrier.try_wait.parity.shared::cta.b64 p, [%1], %2;\n@!p add.s32 %0, %0, 1;\n"
               "setp.lt.and.s32 p, %0, %3, !p;\n@p bra.uni W;\n}\n" : "+r"(n) : "r"(bar), "r"(parity), "n"(SPIN_LIMIT) : "memory");
}
__device__ __forceinline__ void flag_add(int f) {
  asm volatile("red.relaxed.gpu.global.add.u32 [%0], 1;" ::"l"(g_flag + f * FS) : "memory");
}
__device__ __forceinline__ void flag_wait(int f, uint32_t target) {
  uint32_t v; int it = 0;
  do {
    asm volatile("ld.acquire.gpu.global.u32 %0, [%1];" : "=r"(v) : "l"(g_flag + f * FS) : "memory");
    spin_check(it);
  } while ((int)(v - target) < 0);
}
__device__ __forceinline__ void flag_peek(uint32_t dst, int f) {
  asm volatile("cp.async.cg.shared.global [%0], [%1], 16;\ncp.async.commit_group;" ::"r"(dst), "l"(g_flag + f * FS) : "memory");
}
__device__ __forceinline__ bool flag_seen(uint32_t src, uint32_t ep1) {
  uint32_t v;
  asm volatile("cp.async.wait_group 0;\nld.shared.u32 %0, [%1];" : "=r"(v) : "r"(src) : "memory");
  return (int)(v - 8 * ep1) >= 0;
}
__device__ __forceinline__ void fence_async_global() { asm volatile("fence.proxy.async.global;" ::: "memory"); }
__device__ __forceinline__ void fence_async_smem() { asm volatile("fence.proxy.async.shared::cta;" ::: "memory"); }
__device__ __forceinline__ void tma2d(uint32_t dst, const CUtensorMap* m, uint32_t bar, int c0, int c1) {
  asm volatile("cp.async.bulk.tensor.2d.shared::cluster.global.mbarrier::complete_tx::bytes [%0], [%1, {%3, %4}], [%2];"
               ::"r"(dst), "l"(m), "r"(bar), "r"(c0), "r"(c1) : "memory");
}
__device__ __forceinline__ void bulk_s2s(uint32_t dst_cl, uint32_t src, uint32_t bytes, uint32_t bar_cl) {
  asm volatile("cp.async.bulk.shared::cluster.shared::cta.mbarrier::complete_tx::bytes [%0], [%1], %2, [%3];" ::"r"(dst_cl), "r"(src), "r"(bytes), "r"(bar_cl) : "memory");
}
__device__ __forceinline__ void map_prefetch(const CUtensorMap* m) { asm volatile("prefetch.tensormap [%0];" ::"l"(m) : "memory"); }
__device__ __forceinline__ void tma2d_mc(uint32_t dst, const CUtensorMap* m, uint32_t bar, int c0, int c1, uint16_t mask = 3) {
  asm volatile("cp.async.bulk.tensor.2d.shared::cluster.global.mbarrier::complete_tx::bytes.multicast::cluster [%0], [%1, {%3, %4}], [%2], %5;"
               ::"r"(dst), "l"(m), "r"(bar), "r"(c0), "r"(c1), "h"(mask) : "memory");
}
__device__ __forceinline__ void tma3d(uint32_t dst, const CUtensorMap* m, uint32_t bar, int c0, int c1, int c2) {
  asm volatile("cp.async.bulk.tensor.3d.shared::cluster.global.mbarrier::complete_tx::bytes [%0], [%1, {%3, %4, %5}], [%2];"
               ::"r"(dst), "l"(m), "r"(bar), "r"(c0), "r"(c1), "r"(c2) : "memory");
}
__device__ __forceinline__ void tma4d(uint32_t dst, const CUtensorMap* m, uint32_t bar, int c0, int c1, int c2, int c3) {
  asm volatile("cp.async.bulk.tensor.4d.shared::cluster.global.mbarrier::complete_tx::bytes [%0], [%1, {%3, %4, %5, %6}], [%2];"
               ::"r"(dst), "l"(m), "r"(bar), "r"(c0), "r"(c1), "r"(c2), "r"(c3) : "memory");
}
__device__ __forceinline__ void tma3d_mc(uint32_t dst, const CUtensorMap* m, uint32_t bar, int c0, int c1, int c2) {
  asm volatile("cp.async.bulk.tensor.3d.shared::cluster.global.mbarrier::complete_tx::bytes.multicast::cluster [%0], [%1, {%3, %4, %5}], [%2], %6;"
               ::"r"(dst), "l"(m), "r"(bar), "r"(c0), "r"(c1), "r"(c2), "h"((uint16_t)3) : "memory");
}
__device__ __forceinline__ void tma2d_st(const CUtensorMap* m, uint32_t src, int c0, int c1) {
  asm volatile("cp.async.bulk.tensor.2d.global.shared::cta.bulk_group [%0, {%2, %3}], [%1];" ::"l"(m), "r"(src), "r"(c0), "r"(c1) : "memory");
}
__device__ __forceinline__ void tma3d_st(const CUtensorMap* m, uint32_t src, int c0, int c1, int c2) {
  asm volatile("cp.async.bulk.tensor.3d.global.shared::cta.bulk_group [%0, {%2, %3, %4}], [%1];" ::"l"(m), "r"(src), "r"(c0), "r"(c1), "r"(c2) : "memory");
}
__device__ __forceinline__ void bulk_commit() { asm volatile("cp.async.bulk.commit_group;" ::: "memory"); }
__device__ __forceinline__ void bulk_wait_read() { asm volatile("cp.async.bulk.wait_group.read 0;" ::: "memory"); }
__device__ __forceinline__ void bulk_wait_all() { asm volatile("cp.async.bulk.wait_group 0;" ::: "memory"); }
__device__ __forceinline__ void wg_fence() { asm volatile("wgmma.fence.sync.aligned;" ::: "memory"); }
__device__ __forceinline__ void wg_commit() { asm volatile("wgmma.commit_group.sync.aligned;" ::: "memory"); }
template <int N> __device__ __forceinline__ void wg_wait() { asm volatile("wgmma.wait_group.sync.aligned %0;" ::"n"(N) : "memory"); }
template <int N> __device__ __forceinline__ void reg_fence(float (&a)[N]) {
#pragma unroll
  for (int i = 0; i < N; i++) asm volatile("" : "+f"(a[i])::"memory");
}
__device__ __forceinline__ void named_sync(int id, int n) { asm volatile("bar.sync %0, %1;" ::"r"(id), "r"(n) : "memory"); }
__device__ __forceinline__ uint32_t pack2(float lo, float hi) { uint32_t r; asm("cvt.rn.bf16x2.f32 %0, %1, %2;" : "=r"(r) : "f"(hi), "f"(lo)); return r; }
__device__ __forceinline__ uint32_t pack2_relu(float lo, float hi) { uint32_t r; asm("cvt.rn.relu.bf16x2.f32 %0, %1, %2;" : "=r"(r) : "f"(hi), "f"(lo)); return r; }
__device__ __forceinline__ float ex2(float x) { float r; asm("ex2.approx.ftz.f32 %0, %1;" : "=f"(r) : "f"(x)); return r; }
__device__ __forceinline__ float rcp(float x) { float r; asm("rcp.approx.ftz.f32 %0, %1;" : "=f"(r) : "f"(x)); return r; }
__device__ __forceinline__ float bf_lo(uint32_t v) { return __uint_as_float(v << 16); }
__device__ __forceinline__ float bf_hi(uint32_t v) { return __uint_as_float(v & 0xFFFF0000u); }
__device__ __forceinline__ uint4 ldcg128(const void* p) { uint4 v; asm volatile("ld.global.cg.v4.b32 {%0, %1, %2, %3}, [%4];" : "=r"(v.x), "=r"(v.y), "=r"(v.z), "=r"(v.w) : "l"(p)); return v; }
__device__ __forceinline__ void stsm4(uint32_t a, uint32_t r0, uint32_t r1, uint32_t r2, uint32_t r3) {
  asm volatile("stmatrix.sync.aligned.m8n8.x4.shared.b16 [%0], {%1, %2, %3, %4};" ::"r"(a), "r"(r0), "r"(r1), "r"(r2), "r"(r3) : "memory");
}
__device__ __forceinline__ void ldsm4(uint32_t a, uint32_t& r0, uint32_t& r1, uint32_t& r2, uint32_t& r3) {
  asm volatile("ldmatrix.sync.aligned.m8n8.x4.shared.b16 {%0, %1, %2, %3}, [%4];" : "=r"(r0), "=r"(r1), "=r"(r2), "=r"(r3) : "r"(a) : "memory");
}
__device__ __forceinline__ uint32_t movm(uint32_t a) { uint32_t d; asm volatile("movmatrix.sync.aligned.m8n8.trans.b16 %0, %1;" : "=r"(d) : "r"(a)); return d; }
__device__ __forceinline__ void mma16(float (&c)[4], uint32_t a0, uint32_t a1, uint32_t a2, uint32_t a3, uint32_t b0, uint32_t b1) {
  asm volatile("mma.sync.aligned.m16n8k16.row.col.f32.bf16.bf16.f32 {%0,%1,%2,%3}, {%4,%5,%6,%7}, {%8,%9}, {%0,%1,%2,%3};"
               : "+f"(c[0]), "+f"(c[1]), "+f"(c[2]), "+f"(c[3]) : "r"(a0), "r"(a1), "r"(a2), "r"(a3), "r"(b0), "r"(b1));
}
__device__ __forceinline__ void mma8(float (&c)[4], uint32_t a0, uint32_t a1, uint32_t b0) {
  asm volatile("mma.sync.aligned.m16n8k8.row.col.f32.bf16.bf16.f32 {%0,%1,%2,%3}, {%4,%5}, {%6}, {%0,%1,%2,%3};"
               : "+f"(c[0]), "+f"(c[1]), "+f"(c[2]), "+f"(c[3]) : "r"(a0), "r"(a1), "r"(b0));
}
__device__ __forceinline__ float2 lds64f(uint32_t a) { float2 v; asm volatile("ld.shared.v2.f32 {%0, %1}, [%2];" : "=f"(v.x), "=f"(v.y) : "r"(a)); return v; }
__device__ __forceinline__ uint4 lds128(uint32_t a) { uint4 v; asm volatile("ld.shared.v4.b32 {%0, %1, %2, %3}, [%4];" : "=r"(v.x), "=r"(v.y), "=r"(v.z), "=r"(v.w) : "r"(a)); return v; }
__device__ __forceinline__ void sts128(uint32_t a, uint32_t x, uint32_t y, uint32_t z, uint32_t w) { asm volatile("st.shared.v4.b32 [%0], {%1, %2, %3, %4};" ::"r"(a), "r"(x), "r"(y), "r"(z), "r"(w) : "memory"); }
__device__ __forceinline__ void sts64f(uint32_t a, float x, float y) { asm volatile("st.shared.v2.f32 [%0], {%1, %2};" ::"r"(a), "f"(x), "f"(y) : "memory"); }
__device__ __forceinline__ float4 lds128f(uint32_t a) { float4 v; asm volatile("ld.shared.v4.f32 {%0, %1, %2, %3}, [%4];" : "=f"(v.x), "=f"(v.y), "=f"(v.z), "=f"(v.w) : "r"(a)); return v; }
__device__ __forceinline__ void st_tag2(void* p, float x, float y, uint32_t tag) {
  asm volatile("st.relaxed.gpu.global.v2.b32 [%0], {%1, %2};" ::"l"(p), "r"((__float_as_uint(x) & ~3u) | tag), "r"((__float_as_uint(y) & ~3u) | tag) : "memory");
}
__device__ __forceinline__ float4 ld_tag4(const void* p) { float4 v; asm volatile("ld.relaxed.gpu.global.v4.f32 {%0, %1, %2, %3}, [%4];" : "=f"(v.x), "=f"(v.y), "=f"(v.z), "=f"(v.w) : "l"(p) : "memory"); return v; }
__device__ __forceinline__ uint32_t tag_bad(const float4& v, uint32_t tag) {
  return ((__float_as_uint(v.x) ^ tag) | (__float_as_uint(v.y) ^ tag) | (__float_as_uint(v.z) ^ tag) | (__float_as_uint(v.w) ^ tag)) & 3u;
}

template <int F> __device__ __forceinline__ void wgmma4(float (&d)[64], uint32_t a, uint32_t b) { wgmma4_n128<F>(d, a, b); }
template <int F> __device__ __forceinline__ void wgmma4(float (&d)[96], uint32_t a, uint32_t b) { wgmma4_n192<F>(d, a, b); }
template <int F> __device__ __forceinline__ void wgmma4(float (&d)[128], uint32_t a, uint32_t b) { wgmma4_n256<F>(d, a, b); }

struct Ctx { uint32_t sb, bar, ep1; int i, j, rank; };
template <int PH> struct Geo {
  static constexpr int N0 = PH * 16;
  static constexpr int NS = PH == 5 ? 56 : 16;
  static constexpr int NCH = (PH == 0 || PH == 3) ? 4 : (PH == 4 ? 3 : 2);
  static constexpr int SB = 16384 + NCH * 8192;
  static constexpr int DEPTH = NCH == 2 ? 6 : 4;
  static constexpr int SLOT0 = PH == 0 ? 1 : PH == 1 ? 2 : PH == 3 ? 3 : 0;
  static __device__ __forceinline__ int dep(int m) {
    if (PH == 5 && m >= 5 && m <= M5) return m < M5 ? N0 + m - 5 : -1;
    if (m >= DEPTH || PH == 0 || PH == 2) return N0 + m - DEPTH;
    if (PH == 1) return m == 0 ? 12 : 13 + (m >> 1);
    if (PH == 3) return m == 0 ? N0 - 5 : N0 - 4 + m;
    if (PH == 4) return N0 - 3 + (m < 2 ? m : 2);
    return N0 - 4 + (m < 3 ? m : 3);
  }
  static __device__ __forceinline__ int next(int slot, int m) { return slot + 1 == (PH == 5 && m < M5 - 5 ? 5 : DEPTH) ? 0 : slot + 1; }
  static __device__ __forceinline__ int slot_of(int m) { return PH == 5 ? (m >= M5 - 5 ? (m - M5 + 5) % 6 : m % 5) : (SLOT0 + m) % DEPTH; }
  static __device__ __forceinline__ bool own(int m) { return (PH == 2 || PH == 3) && m < 2; }
  static __device__ __forceinline__ bool local(int m) { return (PH == 2 || PH == 3) && m < 4; }
  static __device__ __forceinline__ int koff(int m, int j) {
    if (local(m)) return (128 * j) ^ (64 * m);
    if (PH == 2 || PH == 3) { const int t = m < 10 ? m - 4 : m - 10; return 128 * (t < (j & 6) ? t : t + 2) + (m < 10 ? 0 : 64); }
    if (PH == 5) return m < 32 ? 448 * (m >> 2) + 64 * (m & 3) : 448 * ((m - 32) / 3) + 256 + 64 * ((m - 32) % 3);
    return 64 * m;
  }
};
__device__ __forceinline__ void wait_empty(const Ctx& c, int d) { mbar_wait(c.bar + 8 * (B_EMPTY + (d & 7)), (d >> 3) & 1); }

__device__ __forceinline__ void set_progress(const Ctx& c, int d) { asm volatile("st.volatile.shared.s32 [%0], %1;" ::"r"(c.bar + 8 * B_PEEK + 16), "r"(d) : "memory"); }
__device__ __forceinline__ void wait_progress(const Ctx& c, int d) {
  asm volatile("{\n.reg .pred p;\n.reg .s32 n, v;\nmov.s32 n, 0;\n"
               "W: ld.volatile.shared.s32 v, [%0];\nsetp.ge.s32 p, v, %1;\n@p bra D;\nnanosleep.u32 %3;\n"
               "add.s32 n, n, 1;\nsetp.lt.s32 p, n, %2;\n@p bra W;\ntrap;\nD:\n}\n" ::"r"(c.bar + 8 * B_PEEK + 16), "r"(d), "n"(SPIN_LIMIT), "n"(NSL) : "memory");
}
static_assert(PACE4 + PACE <= M5 - 6, "the first h1 stores must not wait for slot 5");

template <int PH> __device__ __forceinline__ void produce_b(const Params& p, const Ctx& c, int m0, int m1) {
  using G = Geo<PH>;
  int slot = G::slot_of(m0);
#pragma unroll 1
  for (int m = m0; m < m1; m++) {
    const int n = G::N0 + m, d = G::dep(m);
    if (d >= 0) wait_empty(c, d);
    if (PH == 5 && m == M5) { mbar_wait(c.bar + 8 * B_SEMPTY, 1); mbar_wait(c.bar + 8 * (B_SEMPTY + 1), 1); }
    const uint32_t fb = c.bar + 8 * (n & 7), dst = c.sb + slot * G::SB + 16384;
    mbar_expect_tx(fb, G::own(m) ? G::SB - 16384 : G::SB);
    const int k0 = G::koff(m, c.j);
    if (PH == 0 && m < NA0) { tma3d(dst - 16384, &p.mX, fb, k0, 0, 64 * c.i); tma3d(dst - 8192, &p.mX, fb, k0, 1, 64 * c.i); }
    if (PH == 0) tma4d(dst, &p.mWkv, fb, 0, k0, 2 * c.j, 1);
    if (PH == 1) tma3d(dst, &p.mWq, fb, 0, k0, 2 * c.j);
    if (PH == 2) tma3d(dst, &p.mWo, fb, 0, k0, 2 * c.j);
    if (PH == 3) tma3d(dst, &p.mW1a, fb, 0, k0, 7 * c.j);
    if (PH == 4) tma3d(dst, &p.mW1b, fb, 0, k0, 7 * c.j + 4);
    if (PH == 5) tma3d(dst, &p.mW2, fb, 0, k0, 2 * c.j);
    if (d >= 0) set_progress(c, d);
    if (PH == 0 && m == 0) PROF(2);
    if (PH == 5 && m == MPF) map_prefetch(&p.mOut);
    slot = G::next(slot, m);
  }
}
template <int PH> __device__ __forceinline__ void produce_a(const Params& p, const Ctx& c, bool& seen) {
  using G = Geo<PH>;
  constexpr int M1 = PH == 5 ? 32 : PH == 4 ? 16 : 10;
  const int F0 = (PH == 2 ? F_O : PH == 3 ? F_H : F_H1) + c.i * 4 + c.rank;
  int slot = G::SLOT0;
  const int row = 128 * c.i + 64 * c.rank;
#pragma unroll 1
  for (int m = 0; m < G::NS; m++) {
    if (!G::local(m) && (PH > 0 || m >= NA0)) {
      const int n = G::N0 + m, d = G::dep(m);
      if (m == 4 && (PH == 2 || PH == 3)) { flag_wait(F0, 8 * c.ep1); fence_async_global(); PROF(PH == 2 ? 24 : 26); }
      if (d >= 0) wait_empty(c, d);
      if ((m == M1 && PH >= 2 && PH != 4) || (PH == 5 && m == 0)) {
        if (!seen) { if (!flag_seen(c.bar + 8 * B_PEEK, c.ep1)) flag_wait(F0 + (m ? 2 : 0), 8 * c.ep1); fence_async_global(); }
        PROF(PH == 2 ? 25 : PH == 3 ? 29 : 27 + (m >> 5));
      }
      const uint32_t fb = c.bar + 8 * (n & 7), dst = c.sb + slot * G::SB + c.rank * 8192;
      const int k0 = G::koff(m, c.j);
      if (PH <= 1) tma3d_mc(dst, &p.mX, fb, k0, c.rank, 64 * c.i);
      if (PH == 2) tma2d_mc(dst, &p.mO, fb, k0, row);
      if (PH == 3 || PH == 4) tma2d_mc(dst, &p.mH, fb, k0, row);
      if (PH == 5) tma2d_mc(dst, &p.mH1, fb, k0, row);
      if (PH == 0 && m == NA0) PROF(3);
      if (PH >= 2 && (m == M1 - PK0 || m == M1 - 1)) {
        seen = m == M1 - 1 && flag_seen(c.bar + 8 * B_PEEK, c.ep1);
        if (seen) fence_async_global(); else flag_peek(c.bar + 8 * B_PEEK, F0 + (PH == 4 ? 0 : 2));
      }
    }
    slot = G::next(slot, m);
  }
}

struct Con { uint32_t rel, stg, da; int wg, w, lane, spin; bool do_rel; };
template <int PH, bool FIRST, bool RS = false> __device__ __forceinline__ void issue(float (&acc)[Geo<PH>::NCH * 32], const Ctx& c, Con& k, int m, int slot, const uint32_t* ar = nullptr) {
  using G = Geo<PH>;
  const int n = G::N0 + m;
  mbar_wait_u(c.bar + 8 * (n & 7), (n >> 3) & 1, k.spin);
  if (m == 0 && k.do_rel) PROF(32 + 32 * k.wg + 3 * PH);
  if (PH == 2 && (m == 4 || m == 10) && k.do_rel) PROF(32 + 32 * k.wg + 19 + (m >> 3));
  if (PH == 3 && (m == 2 || m == 4) && k.do_rel) PROF(32 + 32 * k.wg + 20 + (m >> 1));
  if (PH == 2 && (m == 2 || m == 3 || m == 5) && k.do_rel) PROF(32 + 32 * k.wg + 22 + m);
  if (PH == 3 && (m == 3 || m == 10) && k.do_rel) PROF(32 + 32 * k.wg + 28 + (m >> 3));
  const uint32_t so = slot * (G::SB >> 4);
  wg_fence();
  if constexpr (RS) wgmma4<FIRST>(acc, ar, so + (((SMEM_BASE + 16384) >> 4) | (512u << 16)));
  else wgmma4<FIRST>(acc, k.da + so, so + (((SMEM_BASE + 16384) >> 4) | (512u << 16)));
  wg_commit();
}
template <int PH> __device__ __forceinline__ void retire(Con& k, int m) {
  wg_wait<1>();
  if (k.do_rel && (PH < 5 || m <= 50)) mbar_arrive_cl(k.rel + 8 * ((Geo<PH>::N0 + m - 1) & 7));
}
template <int PH, int PEND = 0> __device__ __forceinline__ void finish(Con& k) {
  wg_wait<PEND>();
  if (PH < 5 && k.do_rel) mbar_arrive_cl(k.rel + 8 * 7);
  if (k.do_rel) PROF(32 + 32 * k.wg + 3 * PH + 1);
}
template <int PH> __device__ __forceinline__ void steps(float (&acc)[Geo<PH>::NCH * 32], const Ctx& c, Con& k, int m0, int m1) {
  using G = Geo<PH>;
  int slot = G::slot_of(m0);
#pragma unroll 1
  for (int m = m0; m < m1; m++) {
    issue<PH, false>(acc, c, k, m, slot);
    retire<PH>(k, m);
    slot = G::next(slot, m);
  }
}
#define ISSUE(PH, acc, m) issue<PH, false>(acc, c, k, m, Geo<PH>::slot_of(m))
#define ISSUE_RS(PH, acc, r) issue<PH, true, true>(acc, c, k, 0, Geo<PH>::SLOT0, r); issue<PH, false, true>(acc, c, k, 1, Geo<PH>::slot_of(1), r + 16); retire<PH>(k, 1)
#define LAST(PH, acc, on) \
  if (on && k.wg) { pre_load<PH>(pr, c, k); wg_wait<0>(); if (k.do_rel) mbar_arrive_cl(k.rel + 8 * 6); named_sync(4, 256); } \
  ISSUE(PH, acc, 15); \
  if (!(on && k.wg)) { pre_load<PH>(pr, c, k); retire<PH>(k, 15); } \
  finish<PH>(k); \
  if (on && !k.wg) asm volatile("bar.arrive 4, 256;" ::: "memory")
#define ISSUE0(PH, acc) issue<PH, true>(acc, c, k, 0, Geo<PH>::SLOT0)

__device__ __forceinline__ void handoff(const Ctx& c, Con& k, int bar = B_SFULL) {
  fence_async_smem();
  __syncwarp();
  if (k.lane == 0) mbar_arrive(c.bar + 8 * (bar + k.wg));
}

struct Pre { float4 cs[4]; float2 s0, s1; };
template <int PH> __device__ __forceinline__ void pre_load(Pre& a, const Ctx& c, Con& k) {
  if (PH == 0) mbar_wait_u(c.bar + 8 * B_RDY0, 0, k.spin);
  if (PH == 1) { mbar_wait_u(c.bar + 8 * B_RDY1, 0, k.spin); mbar_wait_u(c.bar + 8 * (B_HALO + k.wg), 0, k.spin); }
  if (PH == 4) { mbar_wait_u(c.bar + 8 * B_RDY1, 1, k.spin); mbar_wait_u(c.bar + 8 * (B_SEMPTY + k.wg), 0, k.spin); }
  if (PH == 3) { mbar_wait_u(c.bar + 8 * B_RDY0, 1, k.spin); mbar_wait_u(c.bar + 8 * (B_EMPTY + 4), 1, k.spin); }
  const uint32_t sta = c.sb + OFF_ST + (k.wg * 64 + k.w * 16 + (k.lane >> 2)) * 8;
  a.s0 = lds64f(sta); a.s1 = lds64f(sta + 64);
  a.s0.x = -a.s0.x; a.s1.x = -a.s1.x;
#pragma unroll
  for (int u = 0; u < 4; u++) a.cs[u] = lds128f(c.sb + OFF_CS + (Geo<PH>::NCH == 4 ? 0 : 1024) + (PH == 3 ? u ^ ROT3 : u) * 64 + (k.lane & 3) * 16);
}
template <int PH, int U0, int U1> __device__ __forceinline__ void qkv_pack(uint32_t (&pk)[Geo<PH>::NCH * 8][2], const float (&acc)[Geo<PH>::NCH * 32], Pre& a, const Ctx& c, Con& k) {
  const uint32_t csa = c.sb + OFF_CS + PH * 1024 + (k.lane & 3) * 16;
#pragma unroll
  for (int u = U0; u < U1; u++) {
    const float4 s = a.cs[u & 3];
    if (u + 4 < Geo<PH>::NCH * 4) a.cs[u & 3] = lds128f(csa + (u + 4) * 64);
    float v[8];
#pragma unroll
    for (int e = 0; e < 8; e++) {
      v[e] = fmaf((e & 2) ? a.s1.x : a.s0.x, (e & 4) ? ((e & 1) ? s.w : s.z) : ((e & 1) ? s.y : s.x), acc[8 * u + e]);
      if (PH == 0) v[e] *= (e & 2) ? a.s1.y : a.s0.y;
    }
#pragma unroll
    for (int e = 0; e < 4; e++) pk[2 * u + (e >> 1)][e & 1] = pack2(v[2 * e], v[2 * e + 1]);
  }
}
#define HALO_SRC(kv, H, x) kv[((x) < 8 ? 0 : 8) + 8 * (H) + (x)][1]
template <int H> __device__ __forceinline__ void halo_publish(uint32_t (&kv)[32][2], const Ctx& c, Con& k) {
  const uint32_t ha = k.stg + ((k.w + 1) & 3) * 2048 + k.lane * 16 + H * 8192;
#pragma unroll
  for (int u = 0; u < 4; u++) sts128(ha + u * 512, HALO_SRC(kv, H, 4 * u), HALO_SRC(kv, H, 4 * u + 1), HALO_SRC(kv, H, 4 * u + 2), HALO_SRC(kv, H, 4 * u + 3));
  if (H == 0) return;
  if (k.w == 3) { fence_async_smem(); asm volatile("bar.arrive %0, 64;" ::"r"(5 + k.wg) : "memory"); }
  else { __syncwarp(); if (k.lane == 0) mbar_arrive(c.bar + 8 * (B_HALO + k.wg)); }
}
struct Att { uint32_t hl[16], pp[4][2], z[4]; float l[4][2], mx[4], o[8][4], dn[2][4]; };
template <int H> __device__ __forceinline__ void att_halo(Att& s, Con& k) {
#pragma unroll
  for (int u = 0; u < 4; u++) { const uint4 v = lds128(k.stg + H * 8192 + k.w * 2048 + k.lane * 16 + u * 512); s.hl[4 * u] = v.x; s.hl[4 * u + 1] = v.y; s.hl[4 * u + 2] = v.z; s.hl[4 * u + 3] = v.w; }
}
template <int H> __device__ __forceinline__ void att_qk(Att& s, const uint32_t (&q)[16][2], uint32_t (&kv)[32][2], float lmask, const Ctx& c, Con& k) {
  auto& hl = s.hl; auto& l = s.l;
  const bool g0 = 2 * (k.lane & 3) > (k.lane >> 2), g1 = 2 * (k.lane & 3) + 1 > (k.lane >> 2), nohalo = (k.w == 0 && c.i == 0);
  float sa[2][4], sb[2][4], sh[2][4];
#pragma unroll
  for (int e = 0; e < 8; e++) { sa[e >> 2][e & 3] = 0.f; sb[e >> 2][e & 3] = 0.f; sh[e >> 2][e & 3] = 0.f; }
#pragma unroll
  for (int ks = 0; ks < 2; ks++)
#pragma unroll
    for (int hd = 0; hd < 2; hd++) {
      const int x = 4 * hd + 2 * ks, t = 8 * H + x;
      mma16(sa[hd], q[t][0], q[t][1], q[t + 1][0], q[t + 1][1], kv[t][0], kv[t + 1][0]);
      mma16(sb[hd], q[t][0], q[t][1], q[t + 1][0], q[t + 1][1], kv[t][1], kv[t + 1][1]);
      mma16(sh[hd], q[t][0], q[t][1], q[t + 1][0], q[t + 1][1], hl[x], hl[x + 1]);
    }
#pragma unroll
  for (int t = 16 + 8 * H; t < 24 + 8 * H; t++) if (!MV0) kv[t][0] = movm(kv[t][0]);
#pragma unroll
  for (int hd = 0; hd < 2; hd++) {
    if (nohalo) sh[hd][0] = sh[hd][1] = lmask;
    l[2 * hd][0] = g0 ? sh[hd][0] : sa[hd][0]; l[2 * hd][1] = g1 ? sh[hd][1] : sa[hd][1];
    l[2 * hd + 1][0] = g0 ? sa[hd][2] : sb[hd][2]; l[2 * hd + 1][1] = g1 ? sa[hd][3] : sb[hd][3];
  }
}
__device__ __forceinline__ void att_soft(Att& s, float sc0, float sc1, Con& k) {
  auto& l = s.l; auto& mx = s.mx; auto& pp = s.pp; auto& z = s.z;
  const bool g0 = 2 * (k.lane & 3) > (k.lane >> 2), g1 = 2 * (k.lane & 3) + 1 > (k.lane >> 2);
#pragma unroll
  for (int e = 0; e < 4; e++) mx[e] = fmaxf(l[e][0], l[e][1]);
#pragma unroll
  for (int o = 1; o < 3; o++)
#pragma unroll
    for (int e = 0; e < 4; e++) mx[e] = fmaxf(mx[e], __shfl_xor_sync(~0u, mx[e], o));
#pragma unroll
  for (int e = 0; e < 4; e++) {
    const float sc = (e & 1) ? sc1 : sc0;
    const uint32_t pr = pack2(ex2((l[e][0] - mx[e]) * sc), ex2((l[e][1] - mx[e]) * sc)), mk = (g0 ? 0xFFFFu : 0u) | (g1 ? 0xFFFF0000u : 0u);
    pp[e][0] = pr & mk; pp[e][1] = pr & ~mk; z[e] = pr & (k.spin >> 31);
    mx[e] = __uint_as_float(pr);
  }
}
template <int H> __device__ __forceinline__ void att_pv(Att& s, const uint32_t (&kv)[32][2]) {
  auto& hl = s.hl; auto& mx = s.mx; auto& pp = s.pp; auto& z = s.z; auto& o = s.o; auto& dn = s.dn;
#pragma unroll
  for (int hd = 0; hd < 2; hd++) {
    dn[hd][0] = dn[hd][1] = dn[hd][2] = dn[hd][3] = 0.f;
    mma8(dn[hd], __float_as_uint(mx[2 * hd]), __float_as_uint(mx[2 * hd + 1]), 0x3F803F80u);
  }
#pragma unroll
  for (int t = 0; t < 8; t++) {
    o[t][0] = o[t][1] = o[t][2] = o[t][3] = 0.f;
    mma16(o[t], pp[(t >> 2) * 2][1], pp[(t >> 2) * 2 + 1][0], z[(t >> 2) * 2], pp[(t >> 2) * 2 + 1][1], kv[16 + 8 * H + t][0], kv[16 + 8 * H + t][1]);
  }
#pragma unroll
  for (int t = 0; t < 8; t++) mma8(o[t], pp[(t >> 2) * 2][0], z[(t >> 2) * 2 + 1], hl[8 + t]);
}
template <int H> __device__ __forceinline__ void att_out(Att& s, uint32_t* of, const Ctx& c, Con& k) {
  auto& o = s.o; auto& dn = s.dn;
  const uint32_t oa = k.stg + H * 8192 + (k.w * 16 + (k.lane & 15)) * 128;
#pragma unroll
  for (int u = 0; u < 4; u++) {
    const float r0 = rcp(dn[u >> 1][0]), r1 = rcp(dn[u >> 1][2]);
#pragma unroll
    for (int e = 0; e < 4; e++) of[4 * u + e] = pack2(o[2 * u + (e >> 1)][2 * (e & 1)] * ((e & 1) ? r1 : r0), o[2 * u + (e >> 1)][2 * (e & 1) + 1] * ((e & 1) ? r1 : r0));
    stsm4(oa + (((2 * u + (k.lane >> 4)) ^ (k.lane & 7)) << 4), of[4 * u], of[4 * u + 1], of[4 * u + 2], of[4 * u + 3]);
  }
  handoff(c, k, H == 0 ? B_SFA : B_SFULL);
  if (k.lane == 0) {
    const uint32_t peer = mapa(c.sb, c.rank ^ 1);
    bulk_s2s(peer + (2 + H) * 32768 + k.wg * 8192 + k.w * 2048, k.stg + H * 8192 + k.w * 2048, 2048, peer + OFF_BAR + 8 * (2 + H));
  }
}

__device__ __forceinline__ void res_load(uint32_t (&res)[32], uint32_t bar, uint32_t par, Con& k) {
  mbar_wait_u(bar, par, k.spin);
#pragma unroll
  for (int u = 0; u < 8; u++)
    ldsm4(k.stg + (u >> 2) * 8192 + (k.w * 16 + (k.lane & 15)) * 128 + ((((2 * u & 7) + (k.lane >> 4)) ^ (k.lane & 7)) << 4), res[4 * u], res[4 * u + 1], res[4 * u + 2], res[4 * u + 3]);
}
__device__ __forceinline__ void res_unpack(float (&rf)[64], const uint32_t (&res)[32]) {
#pragma unroll
  for (int x = 0; x < 32; x++) { rf[2 * x] = bf_lo(res[x]); rf[2 * x + 1] = bf_hi(res[x]); }
  if (PREU) reg_fence(rf);
}
template <int CH> __device__ __forceinline__ void epi_res(const float (&acc)[64], const float (&rf)[64], uint32_t (&res)[32], float sc0, float sc1, Con& k) {
  const uint32_t oa = k.stg + CH * 8192 + (k.w * 16 + (k.lane & 15)) * 128;
#pragma unroll
  for (int u = 0; u < 4; u++) {
#pragma unroll
    for (int e = 0; e < 4; e++) {
      const int x = 16 * CH + 4 * u + e;
      const float sc = (e & 1) ? sc1 : sc0;
      res[x] = pack2(fmaf(sc, acc[2 * x], rf[2 * x]), fmaf(sc, acc[2 * x + 1], rf[2 * x + 1]));
    }
    stsm4(oa + (((2 * u + (k.lane >> 4)) ^ (k.lane & 7)) << 4), res[16 * CH + 4 * u], res[16 * CH + 4 * u + 1], res[16 * CH + 4 * u + 2], res[16 * CH + 4 * u + 3]);
  }
}

template <int NCH, int C0, int C1> __device__ __forceinline__ void epi_ffn1(const float (&acc)[NCH * 32], Pre& a, const Ctx& c, Con& k) {
  const uint32_t csa = c.sb + OFF_CS + (NCH == 4 ? 0 : 1024) + (k.lane & 3) * 16;
  const uint32_t rowo = (k.w * 16 + (k.lane & 15)) * 128;
#pragma unroll
  for (int x = C0; x < C1; x++) {
    const int u = NCH == 4 ? x ^ ROT3 : x, ch = u >> 2, t = 8 * u;
    const uint32_t cb = ch < 2 ? k.stg + ch * 8192 : c.sb + OFF_SPARE + k.wg * 8192 + (ch == NCH - 1 ? 16384 : 0);
    const float4 s = a.cs[u & 3];
    const uint32_t v0 = pack2_relu(fmaf(a.s0.x, s.x, acc[t]), fmaf(a.s0.x, s.y, acc[t + 1])), v1 = pack2_relu(fmaf(a.s1.x, s.x, acc[t + 2]), fmaf(a.s1.x, s.y, acc[t + 3]));
    const uint32_t v2 = pack2_relu(fmaf(a.s0.x, s.z, acc[t + 4]), fmaf(a.s0.x, s.w, acc[t + 5])), v3 = pack2_relu(fmaf(a.s1.x, s.z, acc[t + 6]), fmaf(a.s1.x, s.w, acc[t + 7]));
    if (x + 4 < NCH * 4) a.cs[u & 3] = lds128f(csa + (NCH == 4 ? (x + 4) ^ ROT3 : x + 4) * 64);
    stsm4(cb + rowo + ((((2 * u & 7) + (k.lane >> 4)) ^ (k.lane & 7)) << 4), v0, v1, v2, v3);
  }
  if (C1 == 4 * NCH) handoff(c, k);
}

__device__ __forceinline__ void acc_stat(uint32_t v, float sh, float& s1, float& s2) {
  const float x = bf_lo(v) - sh, y = bf_hi(v) - sh;
  s1 += x + y; s2 = fmaf(y, y, fmaf(x, x, s2));
}
template <bool PF> __device__ __forceinline__ void unit_load(const Params& p, int j, int u, uint32_t dst, uint32_t bar) {
  const int ch = u >> 3;
  const CUtensorMap* mp = ch < 6 ? &p.mCq : &p.mC1;
  const int col = ch < 6 ? (ch < 4 ? 1024 + (ch >> 1) * 1024 : 0) + 128 * j + 64 * (ch & 1) : 448 * j + 64 * (ch - 6);
  if (PF) {
    asm volatile("cp.async.bulk.prefetch.tensor.2d.L2.global [%0, {%1, %2}];" ::"l"(mp), "r"(col), "r"((u & 7) * 128) : "memory");
  } else {
    mbar_expect_tx(bar, 16384);
    tma2d(dst, mp, bar, col, (u & 7) * 128);
  }
}
__device__ __forceinline__ void unit_sum(int j, uint32_t tag, int u, uint32_t src, int lane) {
  float s[8];
#pragma unroll
  for (int e = 0; e < 8; e++) s[e] = 0.f;
  uint4 v[2][4];
#pragma unroll
  for (int e = 0; e < 4; e++) v[0][e] = lds128(src + e * 512 + lane * 16);
#pragma unroll 1
  for (int b = 0; b < 4; b++) {
#pragma unroll
    for (int h = 0; h < 2; h++) {
#pragma unroll
      for (int e = 0; e < 4; e++) v[h ^ 1][e] = lds128(src + ((2 * b + h + 1) & 7) * 2048 + e * 512 + lane * 16);
#pragma unroll
      for (int e = 0; e < 4; e++) {
        const uint4 t = v[h][e];
        s[0] += bf_lo(t.x); s[1] += bf_hi(t.x); s[2] += bf_lo(t.y); s[3] += bf_hi(t.y);
        s[4] += bf_lo(t.z); s[5] += bf_hi(t.z); s[6] += bf_lo(t.w); s[7] += bf_hi(t.w);
      }
    }
  }
  const bool hi = lane & 16, md = lane & 8;
#pragma unroll
  for (int e = 0; e < 4; e++) s[e] = (hi ? s[e + 4] : s[e]) + __shfl_xor_sync(~0u, hi ? s[e] : s[e + 4], 16);
#pragma unroll
  for (int e = 0; e < 2; e++) s[e] = (md ? s[e + 2] : s[e]) + __shfl_xor_sync(~0u, md ? s[e] : s[e + 2], 8);
  st_tag2(g_cs + ((u & 7) * 8 + j) * 832 + (u >> 3) * 64 + (lane & 7) * 8 + (lane >> 4) * 4 + (md ? 2 : 0), s[0], s[1], tag);
}
__device__ __forceinline__ void cs_gather(const Ctx& c, int col, int dcol) {
  float4 v[8]; uint32_t bad; int it = 0;
  do {
    bad = 0;
#pragma unroll
    for (int u = 0; u < 8; u++) v[u] = ld_tag4(g_cs + (u * 8 + c.j) * 832 + col);
#pragma unroll
    for (int u = 0; u < 8; u++) bad |= tag_bad(v[u], c.ep1);
    spin_check(it);
  } while (bad);
#pragma unroll
  for (int u = 1; u < 8; u++) { v[0].x += v[u].x; v[0].y += v[u].y; v[0].z += v[u].z; v[0].w += v[u].w; }
  const uint32_t da = c.sb + OFF_CS + (dcol >> 4) * 64 + (dcol & 4) * 8 + (dcol & 8);
  sts64f(da, v[0].x, v[0].y); sts64f(da + 16, v[0].z, v[0].w);
}
__device__ __forceinline__ void aux_warp(const Params& p, const Ctx& c, int a, int lane) {
  const uint32_t spare = c.sb + OFF_SPARE, mystg = c.sb + OFF_STG + a * 16384;
  const uint32_t bA = c.bar + 8 * (B_AUX + a), bSF = c.bar + 8 * (B_SFULL + a), bSE = c.bar + 8 * (B_SEMPTY + a);
  const bool lead = (a == 0 && lane == 0);
  const int row0 = 128 * c.i + 64 * a, u0 = 2 * c.i + a;
  const uint32_t tag = c.ep1 & 3, peer = mapa(c.sb, c.rank ^ 1);
  if (lane == 0) {
    if (a == 0) {
      wait_progress(c, 0);
#pragma unroll
      for (int s = 2; s < 13; s++) map_prefetch(&p.mX + s);
    }
    wait_progress(c, AUX_GATE);
    unit_load<false>(p, c.j, u0, mystg, bA);
  }
  mbar_wait(bA, 0);
  if (lead) PROF(4);
  unit_sum(c.j, tag, u0, mystg, lane);
  if (lead) PROF(6);
  wait_progress(c, G0);
  {
    float4 v; int it = 0;
    do { v = ld_tag4(g_xst + (64 * c.i + 32 * a + lane) * 4); spin_check(it); } while (tag_bad(v, tag));
    sts64f(c.sb + OFF_ST + (32 * a + lane) * 8, v.x, v.y); sts64f(c.sb + OFF_ST + (64 + 32 * a + lane) * 8, v.z, v.w);
  }
#pragma unroll 1
  for (int r = 0; r < 4; r++) {
    if (r == 2) {
      if (lane == 0) {
        mbar_wait(c.bar + 8 * (B_SFA + a), 1);
        tma2d_st(&p.mH, mystg, 128 * c.j, row0); bulk_commit();
        if (lead) PROF(18);
        wait_empty(c, 46);
        bulk_s2s(peer + 1 * 49152 + a * 8192, mystg, 8192, peer + OFF_BAR + 8 * (50 & 7));
        bulk_wait_all(); flag_add(F_H + c.i * 4 + a);
        if (lead) PROF(19);
        mbar_wait(bSF, 1);
        wait_empty(c, 47);
        bulk_s2s(peer + 2 * 49152 + a * 8192, mystg + 8192, 8192, peer + OFF_BAR + 8 * (51 & 7));
        wait_progress(c, 48 + PACEH + a);
        tma2d_st(&p.mH, mystg + 8192, 128 * c.j + 64, row0); bulk_commit();
        bulk_wait_all(); flag_add(F_H + c.i * 4 + 2 + a);
        if (lead) PROF(20);
      }
      __syncwarp();
      if (lane == 0) mbar_arrive(bSE);
      if (lead) PROF(12);
      wait_progress(c, GS);
      {
        float4 v[8]; uint32_t bad; int it = 0;
        do {
          bad = 0;
#pragma unroll
          for (int u = 0; u < 8; u++) v[u] = ld_tag4(g_hst + row0 * 8 + u * 64 + 2 * lane);
#pragma unroll
          for (int u = 0; u < 8; u++) bad |= tag_bad(v[u], tag);
          spin_check(it);
        } while (bad);
        float m0 = 0.f, m1 = 0.f, q0 = 0.f, q1 = 0.f;
#pragma unroll
        for (int u = 0; u < 8; u++) { m0 += v[u].x; m1 += v[u].z; }
        m0 *= 0.125f; m1 *= 0.125f;
#pragma unroll
        for (int u = 0; u < 8; u++) { q0 += fmaf(128.f * (v[u].x - m0), v[u].x - m0, v[u].y); q1 += fmaf(128.f * (v[u].z - m1), v[u].z - m1, v[u].w); }
        sts128(c.sb + OFF_ST + (64 * a + 2 * lane) * 8, __float_as_uint(m0), __float_as_uint(rsqrtf(fmaxf(q0, 0.f) * (1.f / D_) + 1e-5f)),
               __float_as_uint(m1), __float_as_uint(rsqrtf(fmaxf(q1, 0.f) * (1.f / D_) + 1e-5f)));
      }
    }
    const int nl = r == 1 ? 16 : r == 3 ? 24 : 32, dcol = 256 * (r & 1) + 4 * (nl * a + lane);
    if (lane < nl) cs_gather(c, dcol + 384 * (r >> 1), dcol);
    __syncwarp();
    if (lane == 0) { mbar_arrive(c.bar + 8 * (B_RDY0 + (r & 1))); if (lead) PROF(7 + r); }
    if (r == 1) {
      named_sync(5 + a, 64);
      const int hx = (c.i * 8 + c.j) * 2 + a;
      if (lane == 0 && c.i < 15) {
#pragma unroll
        for (int t = 0; t < 2; t++) asm volatile("cp.async.bulk.global.shared::cta.bulk_group [%0], [%1], 2048;" ::"l"(g_halo + hx * 256 + t * 128), "r"(mystg + t * 8192) : "memory");
        bulk_commit(); bulk_wait_all();
        asm volatile("red.relaxed.gpu.global.add.u32 [%0], 1;" ::"l"(g_hflag + hx * HFS) : "memory");
      }
      __syncwarp();
      if (c.i == 0) {
#pragma unroll
        for (int u = 0; u < 8; u++) sts128(mystg + (u >> 2) * 8192 + (u & 3) * 512 + lane * 16, 0, 0, 0, 0);
        __syncwarp();
      }
      if (lane == 0) {
        const uint32_t bH = c.bar + 8 * (B_HALO + a);
        if (c.i == 0) mbar_arrive(bH);
        else {
          uint32_t v; int it = 0;
          do { asm volatile("ld.acquire.gpu.global.u32 %0, [%1];" : "=r"(v) : "l"(g_hflag + (hx - 16) * HFS) : "memory"); spin_check(it); } while ((int)(v - c.ep1) < 0);
          fence_async_global();
          mbar_expect_tx(bH, 4096);
#pragma unroll
          for (int t = 0; t < 2; t++)
            asm volatile("cp.async.bulk.shared::cluster.global.mbarrier::complete_tx::bytes [%0], [%1], 2048, [%2];" ::"r"(mystg + t * 8192), "l"(g_halo + (hx - 16) * 256 + t * 128), "r"(bH) : "memory");
        }
        if (lead) PROF(11);
#pragma unroll 1
        for (int t = 0; t < 2; t++) {
          mbar_wait(t ? bSF : c.bar + 8 * (B_SFA + a), 0);
          tma2d_st(&p.mO, mystg + t * 8192, 128 * c.j + 64 * t, row0); bulk_commit();
          if (lead) PROF(13 + 3 * t);
          bulk_wait_all(); flag_add(F_O + c.i * 4 + 2 * t + a);
          if (lead) PROF(14 + 3 * t);
        }
        wait_progress(c, XR + a * XRA);
        mbar_expect_tx(bSE, 16384);
        tma3d(mystg, &p.mX, bSE, 128 * c.j, a, 64 * c.i); tma3d(mystg + 8192, &p.mX, bSE, 128 * c.j + 64, a, 64 * c.i);
      }
      named_sync(3, 64);
    }
    if (r >= 2) {
      if (lane == 0) {
        const int col = 448 * c.j + 256 * (r - 2);
        mbar_wait(bSF, r & 1);
#pragma unroll 1
        for (int x = r - 2; x < 4; x++) {
          wait_progress(c, r == 2 ? 64 + PACE3 + 2 * x + a : 80 + PACE4 + PACE * (2 * (x - 1) + a));
          tma2d_st(&p.mH1, x < 2 ? spare + x * 16384 + a * 8192 : mystg + (x - 2) * 8192, col + (x < 2 ? (x + 4 - r) * 64 : (x - 2) * 64), row0);
          bulk_commit();
          if (x == 7 - 2 * r) { bulk_wait_read(); mbar_arrive(bSE); }
        }
        bulk_wait_all(); flag_add(F_H1 + c.i * 4 + 2 * (r - 2) + a);
        if (lead) PROF(20 + r);
        if (r == 3) { mbar_expect_tx(bA, 16384); tma2d(mystg, &p.mH, bA, 128 * c.j, row0); tma2d(mystg + 8192, &p.mH, bA, 128 * c.j + 64, row0); }
      }
      __syncwarp();
    }
  }
}

__device__ __forceinline__ void helper_unit(int g, int& j, int& u) {
  const int x = g >> 3;
  j = x < 16 ? x >> 1 : x < 48 ? (x - 16) >> 2 : (x - 48) / 3;
  u = 8 * (x < 16 ? 4 + (x & 1) : x < 48 ? 6 + (x & 3) : 10 + x % 3) + (g & 7);
}
__device__ __forceinline__ void helper_warp(const Params& p, const Ctx& c, int g0, int warp, int lane) {
  const uint32_t buf = c.sb + warp * 16384, bar = c.bar + 8 * (warp < 8 ? warp : warp + B_SEMPTY - 8);
#pragma unroll 1
  for (int t = 0; t < 12; t++) {
    int j, u;
    if (t < 11 && lane == 0) { helper_unit(g0 + 48 * t + 48, j, u); unit_load<true>(p, j, u, 0, 0); }
    helper_unit(g0 + 48 * t, j, u);
    if (lane == 0) unit_load<false>(p, j, u, buf, bar);
    mbar_wait(bar, t & 1);
    unit_sum(j, c.ep1 & 3, u, buf, lane);
  }
}

__device__ __forceinline__ uint32_t load_epoch() {
  uint32_t ctr;
  asm volatile("ld.relaxed.gpu.global.u32 %0, [%1];" : "=r"(ctr) : "l"(&g_ctr) : "memory");
  return (ctr >> 7) + 1;
}

__global__ void __cluster_dims__(2, 1, 1) __launch_bounds__(384, 1) fused_block_kernel(const __grid_constant__ Params p) {
  extern __shared__ __align__(1024) uint8_t smem_raw[];
  Ctx c;
  c.sb = (uint32_t)__cvta_generic_to_shared(smem_raw);
  c.bar = c.sb + OFF_BAR;
  c.rank = blockIdx.x & 1;
  int cl = (blockIdx.x >> 1) + (gridDim.x == 4 ? 64 : 0);
  if (gridDim.x == 132) {
    uint32_t t; asm("mov.u32 %0, %%smid;" : "=r"(t));
    t >>= 1;
    cl = t < 32 ? (t & 7) * 8 + (t >> 3) : t < 60 ? (1 + (t - 32) % 7) * 8 + 4 + (t - 32) / 7 : t < 62 ? t + 4 : t - 58;
  }
  const bool helper = cl >= 64;
  c.i = cl & 15; c.j = ((cl >> 4) & 3) * 2 + c.rank;
  const int warp = __shfl_sync(~0u, threadIdx.x >> 5, 0), lane = threadIdx.x & 31;
  if (warp == 8 && lane == 0) {
    PROF(0);
    map_prefetch(&p.mWkv); map_prefetch(&p.mX);
#pragma unroll
    for (int s = 0; s < 4; s++) mbar_init(c.bar + 8 * s, 1);
    fence_async_smem();
    if (!helper) produce_b<0>(p, c, 0, NB0);
    asm volatile("fence.mbarrier_init.release.cluster;" ::: "memory");
  }
  if (warp == 9 && lane == 0) {
    asm volatile("{\n.reg .pred p;\nsetp.ne.u32 p, %0, %1;\n@p trap;\n}\n" ::"r"(c.sb & 0x3FFFF), "n"(SMEM_BASE));
#pragma unroll
    for (int s = 4; s < B_NUM; s++) mbar_init(c.bar + 8 * s, (s < B_EMPTY || s >= B_SEMPTY) ? 1 : (s >= B_RDY0 ? 2 : 4));
    set_progress(c, -1); __threadfence_block();
    asm volatile("fence.mbarrier_init.release.cluster;" ::: "memory");
    fence_async_smem();
  }
  __syncwarp();
  asm volatile("barrier.cluster.arrive.relaxed.aligned;" ::: "memory");
  asm volatile("barrier.cluster.wait.acquire.aligned;" ::: "memory");
  if (helper) {
    c.ep1 = load_epoch();
    helper_warp(p, c, ((cl & 1) * 2 + c.rank) * 12 + warp, warp, lane);
  } else if (warp >= 8) {
    asm volatile("setmaxnreg.dec.sync.aligned.u32 88;");
    if (warp == 8) {
      if (lane == 0) {
        PROF(1);
        produce_b<0>(p, c, NB0, 16); produce_b<1>(p, c, 0, 16); produce_b<2>(p, c, 0, 16); produce_b<3>(p, c, 0, 16); produce_b<4>(p, c, 0, 16); produce_b<5>(p, c, 0, 56);
        asm volatile("red.relaxed.gpu.global.add.u32 [%0], 1;" ::"l"(&g_ctr) : "memory");
      }
    } else if (warp == 9) {
      if (lane == 0) {
        bool seen = false;
        produce_a<0>(p, c, seen); c.ep1 = load_epoch(); produce_a<1>(p, c, seen); produce_a<2>(p, c, seen); produce_a<3>(p, c, seen); produce_a<4>(p, c, seen); produce_a<5>(p, c, seen);
      }
    } else {
      c.ep1 = load_epoch();
      aux_warp(p, c, warp - 10, lane);
    }
  } else {
    asm volatile("setmaxnreg.inc.sync.aligned.u32 208;");
    c.ep1 = load_epoch();
    Con k;
    k.wg = warp >> 2; k.w = warp & 3; k.lane = lane; k.spin = 0;
    k.do_rel = (threadIdx.x & 127) < 2;
    k.rel = mapa(c.bar + 8 * B_EMPTY, threadIdx.x & 1);
    k.stg = c.sb + OFF_STG + k.wg * 16384;
    k.da = ((SMEM_BASE >> 4) | (1u << 16)) + k.wg * 512;
    uint32_t kv[32][2], res[32]; float accq[64];
    {
      float acc[128]; Pre pr;
      const int rb = 16 * c.j + 2 * warp + (lane >> 4);
      const uint4* xr = reinterpret_cast<const uint4*>(p.x + (size_t)(128 * c.i + rb) * D_) + (lane & 15);
      uint4 xv[8];
      ISSUE0(0, acc);
#pragma unroll
      for (int e = 0; e < 8; e++) xv[e] = ldcg128(xr + 16 * e);
      steps<0>(acc, c, k, 1, XST);
      ISSUE(0, acc, XST);
      const float sh = XSH ? __shfl_sync(~0u, bf_lo(xv[0].x), lane & 16) : 0.f;
      float s1[2] = {0.f, 0.f}, s2[2] = {0.f, 0.f};
#pragma unroll
      for (int e = 0; e < 8; e++) {
        { acc_stat(xv[e].x, sh, s1[0], s2[0]); acc_stat(xv[e].y, sh, s1[1], s2[1]); acc_stat(xv[e].z, sh, s1[0], s2[0]); acc_stat(xv[e].w, sh, s1[1], s2[1]); }
        if (XS3 ? (e & 3) == 3 : e == 4) { asm volatile("" : "+f"(s1[0]), "+f"(s1[1]), "+f"(s2[0]), "+f"(s2[1])); retire<0>(k, XST + (XS3 ? e >> 2 : 0)); ISSUE(0, acc, XST + 1 + (XS3 ? e >> 2 : 0)); }
      }
      float t1 = s1[0] + s1[1], t2 = s2[0] + s2[1];
#pragma unroll
      for (int o = 1; o < 16; o <<= 1) { t1 += __shfl_xor_sync(~0u, t1, o); t2 += __shfl_xor_sync(~0u, t2, o); }
      t1 *= 1.f / D_;
      if ((lane & 15) < 2) st_tag2(g_xst + (64 * c.i + (rb >> 1)) * 4 + 2 * (lane & 1) + (rb & 1), sh + t1, rsqrtf(fmaxf(fmaf(-t1, t1, t2 * (1.f / D_)), 0.f) + 1e-5f), c.ep1 & 3);
      if (threadIdx.x == 0) PROF(5);
      retire<0>(k, XST + 1 + XS3);
      steps<0>(acc, c, k, XST + 2 + XS3, 15);
      LAST(0, acc, (STAG & 1));
      qkv_pack<0, 0, SH0 ? 8 : 16>(kv, acc, pr, c, k);
      ISSUE0(1, accq);
      if (SH0) {
        qkv_pack<0, 8, 10>(kv, acc, pr, c, k);
        ISSUE(1, accq, 1); qkv_pack<0, 10, 12>(kv, acc, pr, c, k); retire<1>(k, 1);
        ISSUE(1, accq, 2); qkv_pack<0, 12, 14>(kv, acc, pr, c, k); retire<1>(k, 2);
        ISSUE(1, accq, 3); qkv_pack<0, 14, 16>(kv, acc, pr, c, k); retire<1>(k, 3);
      }
      if (k.do_rel) PROF(32 + 32 * k.wg + 2);
    }
    {
      float (&acc)[64] = accq; Pre pr; uint32_t q[16][2];
      constexpr int M = 1 + 3 * SH0;
      ISSUE(1, acc, M);
#pragma unroll
      for (int t = 16; t < 32; t++) kv[t][1] = movm(kv[t][1]);
      retire<1>(k, M);
      ISSUE(1, acc, M + 1); halo_publish<0>(kv, c, k); retire<1>(k, M + 1);
      ISSUE(1, acc, M + 2); halo_publish<1>(kv, c, k); retire<1>(k, M + 2);
      if (MV0) {
        ISSUE(1, acc, M + 3);
#pragma unroll
        for (int t = 16; t < 24; t++) kv[t][0] = movm(kv[t][0]);
        retire<1>(k, M + 3);
        ISSUE(1, acc, M + 4);
#pragma unroll
        for (int t = 24; t < 32; t++) kv[t][0] = movm(kv[t][0]);
        retire<1>(k, M + 4);
      }
      steps<1>(acc, c, k, M + 3 + 2 * MV0, 15);
      ISSUE(1, acc, 15); pre_load<1>(pr, c, k);
      const float sc0 = pr.s0.y * 0.25503487f, sc1 = pr.s1.y * 0.25503487f;
      const float lmask = -1.4426950408889634e9f * rcp(sc0);
      Att s0, s1;
      att_halo<0>(s0, k);
      retire<1>(k, 15);
      mbar_wait_u(c.bar + 8 * (B_EMPTY + 5), 1, k.spin);
      finish<1>(k);
      qkv_pack<1, 0, 4>(q, acc, pr, c, k);
      att_qk<0>(s0, q, kv, lmask, c, k); att_soft(s0, sc0, sc1, k); att_pv<0>(s0, kv);
      att_out<0>(s0, res, c, k);
      att_halo<1>(s1, k);
      qkv_pack<1, 4, 8>(q, acc, pr, c, k);
      att_qk<1>(s1, q, kv, lmask, c, k); att_soft(s1, sc0, sc1, k); att_pv<1>(s1, kv);
      att_out<1>(s1, res + 16, c, k);
      if (k.do_rel) PROF(32 + 32 * k.wg + 5);
    }
    {
      float acc[64];
      ISSUE_RS(2, acc, res);
      steps<2>(acc, c, k, 2, 15 - PREU);
      ISSUE(2, acc, 15 - PREU);
      float rf[64];
      res_load(res, c.bar + 8 * (B_SEMPTY + k.wg), 0, k); res_unpack(rf, res);
      if (PREU) { retire<2>(k, 14); ISSUE(2, acc, 15); }
      retire<2>(k, 15);
      finish<2>(k);
      epi_res<0>(acc, rf, res, 1.f, 1.f, k);
      handoff(c, k, B_SFA);
      epi_res<1>(acc, rf, res, 1.f, 1.f, k);
      handoff(c, k);
      if (k.do_rel) PROF(32 + 32 * k.wg + 8);
    }
    {
      float acc4[96], acc[64]; Pre pr;
      {
        float acc3[128];
        ISSUE_RS(3, acc3, res);
        ISSUE(3, acc3, 2); retire<3>(k, 2);
        float s1[2] = {0.f, 0.f}, s2[2] = {0.f, 0.f};
        ISSUE(3, acc3, 3);
#pragma unroll
        for (int e = 0; e < 32; e++) {
          acc_stat(res[e], 0.f, s1[e & 1], s2[e & 1]);
          if (e == 19) { asm volatile("" : "+f"(s1[0]), "+f"(s1[1]), "+f"(s2[0]), "+f"(s2[1])); retire<3>(k, 3); ISSUE(3, acc3, 4); }
        }
        const bool odd = lane & 1;
        float t1 = (odd ? s1[1] : s1[0]) + __shfl_xor_sync(~0u, odd ? s1[0] : s1[1], 1), t2 = (odd ? s2[1] : s2[0]) + __shfl_xor_sync(~0u, odd ? s2[0] : s2[1], 1);
        t1 += __shfl_xor_sync(~0u, t1, 2); t2 += __shfl_xor_sync(~0u, t2, 2);
        if (!(lane & 2)) st_tag2(g_hst + (128 * c.i + 64 * k.wg) * 8 + c.j * 64 + k.w * 16 + (lane >> 2) + 8 * (lane & 1), t1 * (1.f / 128), fmaf(-t1 * (1.f / 128), t1, t2), c.ep1 & 3);
        retire<3>(k, 4);
        steps<3>(acc3, c, k, 5, 15);
        LAST(3, acc3, (STAG & 2));
        if (SH3) {
          epi_ffn1<4, 0, 8>(acc3, pr, c, k);
          ISSUE0(4, acc4); epi_ffn1<4, 8, 10>(acc3, pr, c, k);
          ISSUE(4, acc4, 1); epi_ffn1<4, 10, 13>(acc3, pr, c, k); retire<4>(k, 1);
          ISSUE(4, acc4, 2); epi_ffn1<4, 13, 16>(acc3, pr, c, k); retire<4>(k, 2);
        } else {
          epi_ffn1<4, 0, 16>(acc3, pr, c, k);
          ISSUE0(4, acc4);
        }
        if (k.do_rel) PROF(32 + 32 * k.wg + 11);
      }
      steps<4>(acc4, c, k, SH3 ? 3 : 1, 15);
      ISSUE(4, acc4, 15); pre_load<4>(pr, c, k); retire<4>(k, 15);
      if (SH4) {
        ISSUE0(5, acc);
        finish<4, 1>(k);
        reg_fence(acc4);
        ISSUE(5, acc, 1); epi_ffn1<3, 0, 2>(acc4, pr, c, k); retire<5>(k, 1);
        ISSUE(5, acc, 2); epi_ffn1<3, 2, 4>(acc4, pr, c, k); retire<5>(k, 2);
        ISSUE(5, acc, 3); epi_ffn1<3, 4, 6>(acc4, pr, c, k); retire<5>(k, 3);
        ISSUE(5, acc, 4); epi_ffn1<3, 6, 8>(acc4, pr, c, k); retire<5>(k, 4);
        ISSUE(5, acc, 5); epi_ffn1<3, 8, 10>(acc4, pr, c, k); retire<5>(k, 5);
        ISSUE(5, acc, 6); epi_ffn1<3, 10, 12>(acc4, pr, c, k); retire<5>(k, 6);
      } else {
        finish<4>(k);
        epi_ffn1<3, 0, 12>(acc4, pr, c, k);
        ISSUE0(5, acc);
      }
      if (k.do_rel) PROF(32 + 32 * k.wg + 14);
      steps<5>(acc, c, k, SH4 ? 7 : 1, 55 - PREU);
      ISSUE(5, acc, 55 - PREU);
      const uint32_t sta = c.sb + OFF_ST + (k.wg * 64 + k.w * 16 + (lane >> 2)) * 8;
      const float sc0 = lds64f(sta).y, sc1 = lds64f(sta + 64).y;
      float rf[64];
      res_load(res, c.bar + 8 * (B_AUX + k.wg), 1, k); res_unpack(rf, res);
      if (PREU) ISSUE(5, acc, 55);
      spin_check(k.spin);
      finish<5>(k);
      epi_res<0>(acc, rf, res, sc0, sc1, k);
      fence_async_smem(); __syncwarp();
      if (lane == 0) tma3d_st(&p.mOut, k.stg + k.w * 2048, 128 * c.j, k.wg, 64 * c.i + 16 * k.w);
      epi_res<1>(acc, rf, res, sc0, sc1, k);
      fence_async_smem(); __syncwarp();
      if (k.do_rel) PROF(32 + 32 * k.wg + 17);
      if (lane == 0) { tma3d_st(&p.mOut, k.stg + 8192 + k.w * 2048, 128 * c.j + 64, k.wg, 64 * c.i + 16 * k.w); bulk_commit(); bulk_wait_read(); }
      if (k.do_rel) PROF(32 + 32 * k.wg + 18);
    }
  }
}

typedef CUresult (*EncFn)(CUtensorMap*, CUtensorMapDataType, cuuint32_t, void*, const cuuint64_t*, const cuuint64_t*, const cuuint32_t*,
                          const cuuint32_t*, CUtensorMapInterleave, CUtensorMapSwizzle, CUtensorMapL2promotion, CUtensorMapFloatOOBfill);

void enc(EncFn f, CUtensorMap* m, const void* ptr, int rank, cuuint64_t d0, cuuint64_t d1, cuuint64_t d2, cuuint64_t s1, cuuint64_t s2,
         cuuint32_t b0, cuuint32_t b1, cuuint32_t b2, CUtensorMapSwizzle sw = CU_TENSOR_MAP_SWIZZLE_128B) {
  const cuuint64_t dims[3] = {d0, d1, d2}, str[2] = {s1, s2};
  const cuuint32_t box[3] = {b0, b1, b2}, es[3] = {1, 1, 1};
  f(m, CU_TENSOR_MAP_DATA_TYPE_BFLOAT16, rank, const_cast<void*>(ptr), dims, str, box, es, CU_TENSOR_MAP_INTERLEAVE_NONE,
    sw, CU_TENSOR_MAP_L2_PROMOTION_NONE, CU_TENSOR_MAP_FLOAT_OOB_FILL_NONE);
}

}

extern "C" void kernel_launch(void* const* d_in, const int* in_sizes, int n_in, void* d_out, int out_size) {
  (void)in_sizes; (void)n_in; (void)out_size;
  const void *x = d_in[0], *wqkv = d_in[1], *wo = d_in[2], *w1 = d_in[4], *w2 = d_in[5];
  EncFn f = nullptr;
  cudaDriverEntryPointQueryResult qr;
  cudaGetDriverEntryPoint("cuTensorMapEncodeTiled", (void**)&f, cudaEnableDefault, &qr);
  void *po, *ph, *ph1;
  cudaGetSymbolAddress(&po, g_o); cudaGetSymbolAddress(&ph, g_h); cudaGetSymbolAddress(&ph1, g_h1);
  Params p;
  enc(f, &p.mX, x, 3, D_, 2, S_ / 2, D_ * 2, D_ * 4, 64, 1, 64);
  enc(f, &p.mOut, d_out, 3, D_, 2, S_ / 2, D_ * 2, D_ * 4, 64, 1, 16);
  enc(f, &p.mCq, wqkv, 2, 3 * D_, D_, 1, 3 * D_ * 2, 0, 64, 128, 1, CU_TENSOR_MAP_SWIZZLE_NONE);
  enc(f, &p.mC1, w1, 2, F_, D_, 1, F_ * 2, 0, 64, 128, 1, CU_TENSOR_MAP_SWIZZLE_NONE);
  {
    const cuuint64_t dims[4] = {64, D_, D_ / 64, 3}, str[3] = {3 * D_ * 2, 128, D_ * 2};
    const cuuint32_t box[4] = {64, 64, 2, 2}, es[4] = {1, 1, 1, 1};
    f(&p.mWkv, CU_TENSOR_MAP_DATA_TYPE_BFLOAT16, 4, const_cast<void*>(wqkv), dims, str, box, es, CU_TENSOR_MAP_INTERLEAVE_NONE,
      CU_TENSOR_MAP_SWIZZLE_128B, CU_TENSOR_MAP_L2_PROMOTION_NONE, CU_TENSOR_MAP_FLOAT_OOB_FILL_NONE);
  }
  enc(f, &p.mWq, wqkv, 3, 64, D_, D_ / 64, 3 * D_ * 2, 128, 64, 64, 2);
  enc(f, &p.mWo, wo, 3, 64, D_, D_ / 64, D_ * 2, 128, 64, 64, 2);
  enc(f, &p.mW1a, w1, 3, 64, D_, F_ / 64, F_ * 2, 128, 64, 64, 4);
  enc(f, &p.mW1b, w1, 3, 64, D_, F_ / 64, F_ * 2, 128, 64, 64, 3);
  enc(f, &p.mW2, w2, 3, 64, F_, D_ / 64, D_ * 2, 128, 64, 64, 2);
  enc(f, &p.mO, po, 2, D_, S_, 1, D_ * 2, 0, 64, 64, 1);
  enc(f, &p.mH, ph, 2, D_, S_, 1, D_ * 2, 0, 64, 64, 1);
  enc(f, &p.mH1, ph1, 2, F_, S_, 1, F_ * 2, 0, 64, 64, 1);
  p.x = (const bf16*)x;
  cudaFuncSetAttribute(fused_block_kernel, cudaFuncAttributeMaxDynamicSharedMemorySize, SMEM_BYTES);
  cudaLaunchConfig_t cfg = {};
  cudaLaunchAttribute at;
  at.id = cudaLaunchAttributeClusterDimension; at.val.clusterDim.x = 2; at.val.clusterDim.y = 1; at.val.clusterDim.z = 1;
  cfg.gridDim = dim3(132); cfg.blockDim = dim3(384); cfg.dynamicSmemBytes = SMEM_BYTES; cfg.attrs = &at; cfg.numAttrs = 1;
  int ncl = 0, dev = 0, nsm = 0;
  cudaGetDevice(&dev);
  cudaDeviceGetAttribute(&nsm, cudaDevAttrMultiProcessorCount, dev);
  cudaOccupancyMaxActiveClusters(&ncl, fused_block_kernel, &cfg);
  if (ncl == 66 && nsm == 132) {
    fused_block_kernel<<<132, 384, SMEM_BYTES>>>(p);
  } else {
    fused_block_kernel<<<4, 384, SMEM_BYTES>>>(p);
    fused_block_kernel<<<128, 384, SMEM_BYTES>>>(p);
  }
}
```
